```python
import torch

def _softmax(x, axis=-1):
    return torch.softmax(x, dim=axis)
def _gelu(x):
    return torch.nn.functional.gelu(x, approximate="tanh")
def _silu(x):
    return torch.nn.functional.silu(x)
def _sigmoid(x):
    return torch.sigmoid(x)
def _layernorm(x, axis=-1, eps=1e-5):
    m = x.mean(dim=axis, keepdim=True)
    v = x.var(dim=axis, keepdim=True, unbiased=False)
    return (x - m) / torch.sqrt(v + eps)
def _scatter_add(tgt, idx, src, axis=0):
    return tgt.clone().index_add_(axis, idx, src)
def _segment_sum(src, seg, n):
    out = torch.zeros((n,) + src.shape[1:], dtype=src.dtype)
    return out.index_add_(0, seg, src)
def _pad(x, pw):
    flat = tuple(v for pair in reversed(pw) for v in pair)
    return torch.nn.functional.pad(x, flat)

kernel_name = 'gated_mix__softmax_full_mha__moe_arch_mod__prompt'

def setup_inputs():

    _w = (lambda a: (lambda t: t.to(torch.bfloat16) if t.is_floating_point() else t)(torch.as_tensor(a)))
    def _A_setup():
        B, S, D = 1, 2048, 512
        return {
            "x": _w((lambda *s: torch.randn(*s, dtype=torch.bfloat16) * 0.05)(B, S, D)),
            "wqkv": _w((lambda *s: torch.randn(*s, dtype=torch.bfloat16) * 0.8)(D, 3 * D)),
            "wo": _w((lambda *s: torch.randn(*s, dtype=torch.bfloat16) * 0.1)(D, D)),
        }
    _A_in = _A_setup()

    def _B_setup():
        B, S, D, F, C = 1, 2048, 512, 1792, 2
        return {
            "x": _w((lambda *s: torch.randn(*s, dtype=torch.bfloat16) * 0.05)(B, S, D)),
            "w_r": _w((lambda *s: torch.randn(*s, dtype=torch.bfloat16) * 1.6)(D)),
            "w_gate": _w((lambda *s: torch.randn(*s, dtype=torch.bfloat16) * 0.2)(D, F)),
            "w_up": _w((lambda *s: torch.randn(*s, dtype=torch.bfloat16) * 0.2)(D, F)),
            "w_down": _w((lambda *s: torch.randn(*s, dtype=torch.bfloat16) * 0.2)(F, D)),
        }
    _B_in = _B_setup()

    return {
        "A_x": _A_in["x"],
        "A_wqkv": _A_in["wqkv"],
        "A_wo": _A_in["wo"],
        "B_x": _B_in["x"],
        "B_w_r": _B_in["w_r"],
        "B_w_gate": _B_in["w_gate"],
        "B_w_up": _B_in["w_up"],
        "B_w_down": _B_in["w_down"],
        "gate_w": _w((lambda *s: torch.randn(*s, dtype=torch.bfloat16) * 0.05)(512) * 16.0),
    }

def reference(A_x, A_wqkv, A_wo, B_x, B_w_r, B_w_gate, B_w_up, B_w_down, gate_w):
    def _A_ref(x, wqkv, wo):
        B, S, D = x.shape
        H = 32; Dh = D // H
        qkv = (lambda x, *d: x.permute(*d))((x @ wqkv).reshape(B, S, 3, H, Dh), 2, 0, 3, 1, 4)
        q, k, v = qkv[0], qkv[1], qkv[2]
        scale = Dh ** -0.5
        scores = torch.einsum("bhqd,bhkd->bhqk", q, k) * scale
        p = _softmax(scores, axis=-1)
        o = torch.einsum("bhqk,bhkd->bhqd", p, v)
        return (lambda x, *d: x.permute(*d))(o, 0, 2, 1, 3).reshape(B, S, D) @ wo

    def _B_ref(x, w_r, w_gate, w_up, w_down):
        B, S, D = x.shape
        C = 2
        r = x @ w_r
        idx = torch.argsort(-r, axis=-1)[:, :C]
        idx_e = (lambda x, n, axis: torch.repeat_interleave(x, n, dim=axis))(idx.reshape(B, C, 1), D, axis=2)
        x_sel = (lambda x, i, axis: torch.take_along_dim(x, i, dim=axis))(x, idx_e, axis=1)
        g = _silu(x_sel @ w_gate)
        u = x_sel @ w_up
        y = (g * u) @ w_down
        r_sel = _sigmoid((lambda x, i, axis: torch.take_along_dim(x, i, dim=axis))(r, idx, axis=1))
        y = y * r_sel.reshape(B, C, 1)
        b_off = (torch.arange(B) * S).reshape(B, 1)
        flat_idx = (idx + b_off).reshape(B * C)
        zero = (x * 0.0).reshape(B * S, D)
        upd = _scatter_add(zero, flat_idx, y.reshape(B * C, D), axis=0)
        return x + upd.reshape(B, S, D)

    x = A_x
    g = _sigmoid((x * gate_w).sum(-1, keepdims=True))
    a = _A_ref(x, A_wqkv, A_wo)
    b = _B_ref(x, B_w_r, B_w_gate, B_w_up, B_w_down)
    return g * a + (1 - g) * b
```

```cpp
#include <cuda_runtime.h>
#include <cuda_bf16.h>
#include <cuda_fp16.h>
#include <cuda.h>
#include <stdint.h>

namespace {

constexpr int S_ = 2048, D_ = 512, F_ = 1792;
constexpr int NCTA = 132;
constexpr uint32_t SBASE = 0x400;
constexpr int SMEM_BYTES = 232448;

constexpr int A_STAGES = 5, A_STAGE_BYTES = 40960;
constexpr int OFF_XCH = A_STAGES * A_STAGE_BYTES;
constexpr int OFF_K = 0, OFF_ONE = 98304, OFF_VHI = 98560;
constexpr int OFF_WO1 = 132096;
constexpr int OFF_O = 0, OFF_WO2 = 65536;
constexpr int OFF_MISC = 230400;
constexpr int M_STAGES = 6, M_STAGE_BYTES = 32768;
constexpr int OFF_XSEL = M_STAGES * M_STAGE_BYTES, OFF_HSEL = OFF_XSEL + 8192;
constexpr int B_FULL = 0, B_EMPTY = 8, B_KV = 16, B_WO1 = 24, B_WO2 = 25, B_O = 26, NBAR = 30;

#define EXP_PAT 0x3333003333330033ull
constexpr unsigned long long PAT = EXP_PAT;
__host__ __device__ constexpr int pat_of(int i) { return (int)((PAT >> (4 * i)) & 15); }
__host__ __device__ constexpr bool cg_scaled(int cg) { return pat_of(2 * cg) == 2 || pat_of(2 * cg) == 3; }
constexpr float U0 = 90.f;
constexpr float OFF_C = 1.580014f, OFF_E = 0.087454f;
__host__ __device__ constexpr float init_of(int i) {
    return pat_of(i) == 0 ? (U0 - 127.f) : pat_of(i) == 2 ? 128.f + 0.5f * (U0 - OFF_C)
         : pat_of(i) == 3 ? 128.f + 0.5f * (U0 - OFF_E) : 256.f + (U0 - OFF_C);
}
constexpr float BOUND_MAX = 30.f;
constexpr float QSCALE = 0.25f * 1.4426950408889634f;

__device__ uint4 g_q[32 * 32 * 128];
__device__ __align__(1024) uint8_t g_k[32 * 65536];
__device__ __align__(1024) uint8_t g_v[32 * 65536];
__device__ __align__(1024) uint8_t g_o[32 * 65536];
__device__ __align__(16) float g_kmax[32 * 128];
__device__ __align__(16) float g_r[S_];
__device__ __align__(16) float g_g[S_];
__device__ __align__(16) float g_y[4 * 2 * D_];
__device__ __align__(16) int g_sel[4];
__device__ uint32_t g_cnt[16 * 32];
__device__ uint32_t g_epoch[NCTA];
#define TSTAMP(i)

__device__ __forceinline__ void wg_ss_n192_bt(float (&d)[96], uint64_t da, uint64_t db, int acc) {
  asm volatile("{\n.reg .pred p;\nsetp.ne.b32 p, %98, 0;\n"
      "wgmma.mma_async.sync.aligned.m64n192k16.f32.bf16.bf16 {%0,%1,%2,%3,%4,%5,%6,%7,%8,%9,%10,%11,%12,%13,%14,%15,%16,%17,%18,%19,%20,%21,%22,%23,"
      "%24,%25,%26,%27,%28,%29,%30,%31,%32,%33,%34,%35,%36,%37,%38,%39,%40,%41,%42,%43,%44,%45,%46,%47,"
      "%48,%49,%50,%51,%52,%53,%54,%55,%56,%57,%58,%59,%60,%61,%62,%63,%64,%65,%66,%67,%68,%69,%70,%71,"
      "%72,%73,%74,%75,%76,%77,%78,%79,%80,%81,%82,%83,%84,%85,%86,%87,%88,%89,%90,%91,%92,%93,%94,%95}, %96, %97, p, 1, 1, 0, 1;\n}\n"
    : "+f"(d[0]), "+f"(d[1]), "+f"(d[2]), "+f"(d[3]), "+f"(d[4]), "+f"(d[5]), "+f"(d[6]), "+f"(d[7]), "+f"(d[8]), "+f"(d[9]), "+f"(d[10]), "+f"(d[11]),
      "+f"(d[12]), "+f"(d[13]), "+f"(d[14]), "+f"(d[15]), "+f"(d[16]), "+f"(d[17]), "+f"(d[18]), "+f"(d[19]), "+f"(d[20]), "+f"(d[21]), "+f"(d[22]), "+f"(d[23]),
      "+f"(d[24]), "+f"(d[25]), "+f"(d[26]), "+f"(d[27]), "+f"(d[28]), "+f"(d[29]), "+f"(d[30]), "+f"(d[31]), "+f"(d[32]), "+f"(d[33]), "+f"(d[34]), "+f"(d[35]),
      "+f"(d[36]), "+f"(d[37]), "+f"(d[38]), "+f"(d[39]), "+f"(d[40]), "+f"(d[41]), "+f"(d[42]), "+f"(d[43]), "+f"(d[44]), "+f"(d[45]), "+f"(d[46]), "+f"(d[47]),
      "+f"(d[48]), "+f"(d[49]), "+f"(d[50]), "+f"(d[51]), "+f"(d[52]), "+f"(d[53]), "+f"(d[54]), "+f"(d[55]), "+f"(d[56]), "+f"(d[57]), "+f"(d[58]), "+f"(d[59]),
      "+f"(d[60]), "+f"(d[61]), "+f"(d[62]), "+f"(d[63]), "+f"(d[64]), "+f"(d[65]), "+f"(d[66]), "+f"(d[67]), "+f"(d[68]), "+f"(d[69]), "+f"(d[70]), "+f"(d[71]),
      "+f"(d[72]), "+f"(d[73]), "+f"(d[74]), "+f"(d[75]), "+f"(d[76]), "+f"(d[77]), "+f"(d[78]), "+f"(d[79]), "+f"(d[80]), "+f"(d[81]), "+f"(d[82]), "+f"(d[83]),
      "+f"(d[84]), "+f"(d[85]), "+f"(d[86]), "+f"(d[87]), "+f"(d[88]), "+f"(d[89]), "+f"(d[90]), "+f"(d[91]), "+f"(d[92]), "+f"(d[93]), "+f"(d[94]), "+f"(d[95])
    : "l"(da), "l"(db), "r"(acc));
}
__device__ __forceinline__ void wg_ss_n64_bt(float (&d)[32], uint64_t da, uint64_t db, int acc) {
  asm volatile("{\n.reg .pred p;\nsetp.ne.b32 p, %34, 0;\n"
      "wgmma.mma_async.sync.aligned.m64n64k16.f32.bf16.bf16 {%0,%1,%2,%3,%4,%5,%6,%7,%8,%9,%10,%11,%12,%13,%14,%15,%16,%17,%18,%19,%20,%21,%22,%23,"
      "%24,%25,%26,%27,%28,%29,%30,%31}, %32, %33, p, 1, 1, 0, 1;\n}\n"
    : "+f"(d[0]), "+f"(d[1]), "+f"(d[2]), "+f"(d[3]), "+f"(d[4]), "+f"(d[5]), "+f"(d[6]), "+f"(d[7]), "+f"(d[8]), "+f"(d[9]), "+f"(d[10]), "+f"(d[11]),
      "+f"(d[12]), "+f"(d[13]), "+f"(d[14]), "+f"(d[15]), "+f"(d[16]), "+f"(d[17]), "+f"(d[18]), "+f"(d[19]), "+f"(d[20]), "+f"(d[21]), "+f"(d[22]), "+f"(d[23]),
      "+f"(d[24]), "+f"(d[25]), "+f"(d[26]), "+f"(d[27]), "+f"(d[28]), "+f"(d[29]), "+f"(d[30]), "+f"(d[31])
    : "l"(da), "l"(db), "r"(acc));
}
__device__ __forceinline__ void wg_ss_n8_at(float (&d)[4], uint64_t da, uint64_t db, int acc) {
  asm volatile("{\n.reg .pred p;\nsetp.ne.b32 p, %6, 0;\n"
      "wgmma.mma_async.sync.aligned.m64n8k16.f32.bf16.bf16 {%0,%1,%2,%3}, %4, %5, p, 1, 1, 1, 0;\n}\n"
    : "+f"(d[0]), "+f"(d[1]), "+f"(d[2]), "+f"(d[3])
    : "l"(da), "l"(db), "r"(acc));
}
__device__ __forceinline__ void wg_rs_qk(float (&d)[32], uint32_t a0, uint32_t a1, uint32_t a2, uint32_t a3, uint64_t db) {
  asm volatile("wgmma.mma_async.sync.aligned.m64n64k16.f32.f16.f16 {%0,%1,%2,%3,%4,%5,%6,%7,%8,%9,%10,%11,%12,%13,%14,%15,%16,%17,%18,%19,%20,%21,%22,%23,"
      "%24,%25,%26,%27,%28,%29,%30,%31}, {%32,%33,%34,%35}, %36, 1, 1, 1, 0;\n"
    : "+f"(d[0]), "+f"(d[1]), "+f"(d[2]), "+f"(d[3]), "+f"(d[4]), "+f"(d[5]), "+f"(d[6]), "+f"(d[7]), "+f"(d[8]), "+f"(d[9]), "+f"(d[10]), "+f"(d[11]),
      "+f"(d[12]), "+f"(d[13]), "+f"(d[14]), "+f"(d[15]), "+f"(d[16]), "+f"(d[17]), "+f"(d[18]), "+f"(d[19]), "+f"(d[20]), "+f"(d[21]), "+f"(d[22]), "+f"(d[23]),
      "+f"(d[24]), "+f"(d[25]), "+f"(d[26]), "+f"(d[27]), "+f"(d[28]), "+f"(d[29]), "+f"(d[30]), "+f"(d[31])
    : "r"(a0), "r"(a1), "r"(a2), "r"(a3), "l"(db));
}
__device__ __forceinline__ void wg_rs_pv(float (&d)[12], uint32_t a0, uint32_t a1, uint32_t a2, uint32_t a3, uint64_t db) {
  asm volatile("wgmma.mma_async.sync.aligned.m64n24k16.f32.bf16.bf16 {%0,%1,%2,%3,%4,%5,%6,%7,%8,%9,%10,%11}, {%12,%13,%14,%15}, %16, 1, 1, 1, 0;\n"
    : "+f"(d[0]), "+f"(d[1]), "+f"(d[2]), "+f"(d[3]), "+f"(d[4]), "+f"(d[5]), "+f"(d[6]), "+f"(d[7]), "+f"(d[8]), "+f"(d[9]), "+f"(d[10]), "+f"(d[11])
    : "r"(a0), "r"(a1), "r"(a2), "r"(a3), "l"(db));
}

__device__ __forceinline__ void wg_fence() { asm volatile("wgmma.fence.sync.aligned;" ::: "memory"); }
__device__ __forceinline__ void wg_commit() { asm volatile("wgmma.commit_group.sync.aligned;" ::: "memory"); }
template <int N> __device__ __forceinline__ void wg_wait() { asm volatile("wgmma.wait_group.sync.aligned %0;" ::"n"(N) : "memory"); }
template <int N> __device__ __forceinline__ void reg_fence(float (&r)[N]) {
#pragma unroll
    for (int i = 0; i < N; i++) asm volatile("" : "+f"(r[i])::"memory");
}
__device__ __forceinline__ void mbar_init(uint32_t bar, int cnt) { asm volatile("mbarrier.init.shared::cta.b64 [%0], %1;" ::"r"(bar), "r"(cnt) : "memory"); }
__device__ __forceinline__ void mbar_expect(uint32_t bar, int bytes) { asm volatile("mbarrier.arrive.expect_tx.shared::cta.b64 _, [%0], %1;" ::"r"(bar), "r"(bytes) : "memory"); }
__device__ __forceinline__ void mbar_arrive(uint32_t bar) { asm volatile("mbarrier.arrive.shared::cta.b64 _, [%0];" ::"r"(bar) : "memory"); }
__device__ __forceinline__ void mbar_wait(uint32_t bar, int parity) {
    asm volatile("{\n.reg .pred p;\n.reg .u32 n;\nmov.u32 n, 0;\n"
                 "W_%=:\nmbarrier.try_wait.parity.shared::cta.b64 p, [%0], %1;\n@p bra D_%=;\n"
                 "add.u32 n, n, 1;\nsetp.lt.u32 p, n, 0x4000000;\n@p bra W_%=;\ntrap;\nD_%=:\n}" ::"r"(bar), "r"(parity) : "memory");
}
__device__ __forceinline__ void tma2d(uint32_t dst, const CUtensorMap* m, int c0, int c1, uint32_t bar) {
    asm volatile("cp.async.bulk.tensor.2d.shared::cluster.global.mbarrier::complete_tx::bytes [%0], [%1, {%2, %3}], [%4];"
                 ::"r"(dst), "l"(m), "r"(c0), "r"(c1), "r"(bar) : "memory");
}
__device__ __forceinline__ void bulk_ld(uint32_t dst, const void* src, int bytes, uint32_t bar) {
    asm volatile("cp.async.bulk.shared::cluster.global.mbarrier::complete_tx::bytes [%0], [%1], %2, [%3];"
                 ::"r"(dst), "l"(src), "r"(bytes), "r"(bar) : "memory");
}
__device__ __forceinline__ void fence_async_s() { asm volatile("fence.proxy.async.shared::cta;" ::: "memory"); }
__device__ __forceinline__ void fence_async_g() { asm volatile("fence.proxy.async.global;" ::: "memory"); }
__device__ __forceinline__ void cnt_arrive(int i) {
    asm volatile("red.release.gpu.global.add.u32 [%0], 1;" ::"l"(&g_cnt[i * 32]) : "memory");
}
__device__ __forceinline__ void cnt_wait(int i, uint32_t target) {
    for (uint32_t n = 0;; n++) {
        uint32_t v;
        asm volatile("ld.acquire.gpu.global.u32 %0, [%1];" : "=r"(v) : "l"(&g_cnt[i * 32]) : "memory");
        if ((int)(v - target) >= 0) break;
        if (n > 0x800000u) __trap();
    }
}
__device__ __forceinline__ void named_sync(int id, int n) { asm volatile("bar.sync %0, %1;" ::"r"(id), "r"(n) : "memory"); }
__device__ __forceinline__ uint32_t pack_h2(float lo, float hi) { uint32_t r; asm("cvt.rn.f16x2.f32 %0, %1, %2;" : "=r"(r) : "f"(hi), "f"(lo)); return r; }
__device__ __forceinline__ uint32_t pack_b2(float lo, float hi) { uint32_t r; asm("cvt.rn.bf16x2.f32 %0, %1, %2;" : "=r"(r) : "f"(hi), "f"(lo)); return r; }
__device__ __forceinline__ float blo(uint32_t v) { return __uint_as_float(v << 16); }
__device__ __forceinline__ float bhi(uint32_t v) { return __uint_as_float(v & 0xffff0000u); }
__device__ __forceinline__ float rbf(float v) { return __bfloat162float(__float2bfloat16_rn(v)); }
__device__ __forceinline__ float frcp(float v) { float r; asm("rcp.approx.f32 %0, %1;" : "=f"(r) : "f"(v)); return r; }
__device__ __forceinline__ float sigmoidf_(float v) { return frcp(1.f + __expf(-v)); }
__host__ __device__ constexpr uint64_t mkdesc(uint32_t off, uint32_t lbo, uint32_t sbo, uint32_t swz) {
    return (uint64_t)((SBASE + off) >> 4) | ((uint64_t)(lbo >> 4) << 16) | ((uint64_t)(sbo >> 4) << 32) | ((uint64_t)swz << 62);
}

template <int T> __device__ __forceinline__ uint32_t exp_pair(float a, float b, uint32_t c7f) {
    uint32_t r;
    if (T == 0) {
        float x, y;
        asm("ex2.approx.ftz.f32 %0, %1;" : "=f"(x) : "f"(a));
        asm("ex2.approx.ftz.f32 %0, %1;" : "=f"(y) : "f"(b));
        r = pack_b2(x, y);
    } else {
        uint32_t y;
        asm("prmt.b32 %0, %1, %2, 0x6521;" : "=r"(y) : "r"(__float_as_uint(a)), "r"(__float_as_uint(b)));
        if (T == 2) {
            uint32_t m = y | 0x3f803f80u, e = y | 0x007f007fu;
            asm("fma.rn.bf16x2 %0, %1, %2, %3;" : "=r"(r) : "r"(y), "r"(m), "r"(e));
        } else if (T == 4) {
            uint32_t m = y | 0x3f803f80u, e;
            asm("lop3.b32 %0, %1, 0x7fff7fff, %2, 0xea;" : "=r"(e) : "r"(y), "r"(c7f));
            asm("fma.rn.bf16x2 %0, %1, %2, %3;" : "=r"(r) : "r"(y), "r"(m), "r"(e));
        } else {
            uint32_t z = 0xfe7ffe7fu - y, w;
            asm("{.reg .b32 c; mov.b32 c, 0x3f103f10; fma.rn.bf16x2 %0, %1, %2, c;}" : "=r"(w) : "r"(y), "r"(z));
            asm("fma.rn.bf16x2 %0, %1, %2, %1;" : "=r"(r) : "r"(y), "r"(w));
        }
    }
    return r;
}
template <int I> struct ExpLoop {
    static __device__ __forceinline__ void run(float (&s)[32], uint32_t (&p)[16], uint32_t c7f) {
        p[I] = exp_pair<pat_of(I)>(s[2 * I], s[2 * I + 1], c7f);
        ExpLoop<I + 1>::run(s, p, c7f);
    }
};
template <> struct ExpLoop<16> { static __device__ __forceinline__ void run(float (&)[32], uint32_t (&)[16], uint32_t) {} };
template <int I> struct InitLoop {
    static __device__ __forceinline__ void run(float (&s)[32]) {
        constexpr float v = init_of(I);
        s[2 * I] = v; s[2 * I + 1] = v;
        InitLoop<I + 1>::run(s);
    }
};
template <> struct InitLoop<16> { static __device__ __forceinline__ void run(float (&)[32]) {} };

constexpr uint64_t DV_STEP = (16ull << 32) - 16ull;

__device__ __forceinline__ void store_o(const float (&o)[12], int rowtile, int head, int warp4, int lane) {
    const float i0 = frcp(o[4]), i1 = frcp(o[6]);
    uint32_t* dst = (uint32_t*)(g_o + rowtile * 65536 + head * 2048 + warp4 * 512) + lane;
    dst[0] = pack_b2(o[0] * i0, o[1] * i0);
    dst[32] = pack_b2(o[8] * i0, o[9] * i0);
    dst[64] = pack_b2(o[2] * i1, o[3] * i1);
    dst[96] = pack_b2(o[10] * i1, o[11] * i1);
}

__device__ __noinline__ void attn_slow(uint8_t* smem, const __nv_bfloat16* x, const __nv_bfloat16* w, int head, int rg) {
    const int tid = threadIdx.x;
    float q[16];
    for (int it = 0; it < 5; it++) {
        const int tok = it < 4 ? it * 512 + tid : rg * 512 + tid;
        const __nv_bfloat16* wc = w + (it < 4 ? 512 : 0) + head * 16;
        float a[16];
#pragma unroll
        for (int d = 0; d < 16; d++) a[d] = 0.f;
        for (int k8 = 0; k8 < 64; k8++) {
            const uint4 xv = *(const uint4*)(x + tok * D_ + k8 * 8);
            const uint32_t xs[4] = {xv.x, xv.y, xv.z, xv.w};
#pragma unroll
            for (int kk = 0; kk < 8; kk++) {
                const float xf = (kk & 1) ? bhi(xs[kk >> 1]) : blo(xs[kk >> 1]);
                const uint4 w0 = *(const uint4*)(wc + (k8 * 8 + kk) * 1536), w1 = *(const uint4*)(wc + (k8 * 8 + kk) * 1536 + 8);
                const uint32_t ws[8] = {w0.x, w0.y, w0.z, w0.w, w1.x, w1.y, w1.z, w1.w};
#pragma unroll
                for (int d = 0; d < 8; d++) { a[2 * d] += xf * blo(ws[d]); a[2 * d + 1] += xf * bhi(ws[d]); }
            }
        }
        if (it < 4) {
#pragma unroll
            for (int d = 0; d < 8; d++) ((uint32_t*)(smem + OFF_K + tok * 32))[d] = pack_b2(a[2 * d], a[2 * d + 1]);
        } else {
#pragma unroll
            for (int d = 0; d < 16; d++) q[d] = rbf(a[d]);
        }
    }
    __syncthreads();
    auto score = [&](int tok) {
        const uint4 k0 = *(const uint4*)(smem + OFF_K + tok * 32), k1 = *(const uint4*)(smem + OFF_K + tok * 32 + 16);
        const uint32_t ks[8] = {k0.x, k0.y, k0.z, k0.w, k1.x, k1.y, k1.z, k1.w};
        float s = 0.f;
#pragma unroll
        for (int d = 0; d < 8; d++) { s += q[2 * d] * blo(ks[d]); s += q[2 * d + 1] * bhi(ks[d]); }
        return rbf(rbf(s) * 0.25f);
    };
    float m = -INFINITY, l = 0.f;
    for (int tok = 0; tok < S_; tok++) {
        const float s = score(tok), mn = fmaxf(m, s);
        l = l * __expf(m - mn) + __expf(s - mn);
        m = mn;
    }
    const float il = frcp(l);
    float o[16];
#pragma unroll
    for (int d = 0; d < 16; d++) o[d] = 0.f;
    for (int t8 = 0; t8 < S_ / 8; t8++) {
        float p[8];
#pragma unroll
        for (int j = 0; j < 8; j++) p[j] = rbf(__expf(score(t8 * 8 + j) - m) * il);
        const int T = t8 >> 4, b = (T >> 3) * 16 + (t8 & 15), cg = T & 7, ch = 4 * b + (cg >> 1);
        const uint8_t* vlo = smem + OFF_ONE - 256 * (ch + 1) + (cg & 1) * 128;
        const uint8_t* vhi = smem + OFF_ONE + 256 * (ch + 1) + (cg & 1) * 128;
#pragma unroll
        for (int d = 0; d < 16; d++) {
            const uint4 v = *(const uint4*)((d < 8 ? vlo : vhi) + (d & 7) * 16);
            o[d] += p[0] * blo(v.x) + p[1] * bhi(v.x) + p[2] * blo(v.y) + p[3] * bhi(v.y) + p[4] * blo(v.z) + p[5] * bhi(v.z) + p[6] * blo(v.w) + p[7] * bhi(v.w);
        }
    }
    const int row = rg * 512 + tid;
    uint8_t* dst = g_o + (row >> 6) * 65536 + head * 2048 + ((row >> 3) & 7) * 256 + (row & 7) * 16;
    *(uint4*)dst = make_uint4(pack_b2(o[0], o[1]), pack_b2(o[2], o[3]), pack_b2(o[4], o[5]), pack_b2(o[6], o[7]));
    *(uint4*)(dst + 128) = make_uint4(pack_b2(o[8], o[9]), pack_b2(o[10], o[11]), pack_b2(o[12], o[13]), pack_b2(o[14], o[15]));
}

struct Params {
    const __nv_bfloat16 *x, *wqkv, *w_r, *gate_w;
    __nv_bfloat16* out;
    int mode;
};

__device__ __forceinline__ void mod_cta(uint8_t* smem, uint32_t sb, const Params& P, const CUtensorMap* mg, const CUtensorMap* mu,
                                     const CUtensorMap* md, uint32_t ep) {
    const int tid = threadIdx.x, lane = tid & 31, warp = tid >> 5, wg = tid >> 7, part = blockIdx.x - 128;
    const uint32_t bars = sb + OFF_MISC;
    constexpr int NBOX = 44;
    auto issue = [&](int i) {
        const int st = i % M_STAGES;
        const uint32_t bar = bars + 8 * (B_FULL + st), dst = sb + st * M_STAGE_BYTES;
        if (i < 28) {
            mbar_expect(bar, 32768);
            tma2d(dst, (i & 2) ? mu : mg, part * 448 + (i >> 2) * 64, (i & 1) * 256, bar);
        } else {
            mbar_expect(bar, 28672);
            tma2d(dst, md, ((i - 28) >> 1) * 64, part * 448 + (i & 1) * 224, bar);
        }
    };
    if (tid == 0)
        for (int i = 0; i < M_STAGES; i++) issue(i);
    for (int i = tid; i < 4096; i += 512) ((uint32_t*)(smem + OFF_XSEL))[i] = 0;
    if (tid == 0) cnt_wait(12, 128 * ep);
    __syncthreads();
    unsigned long long b1 = 0, b2 = 0;
    {
        const float4 rv = *(const float4*)(g_r + tid * 4);
        const float rr[4] = {rv.x, rv.y, rv.z, rv.w};
#pragma unroll
        for (int j = 0; j < 4; j++) {
            uint32_t u = __float_as_uint(rr[j]);
            u = (u & 0x80000000u) ? ~u : (u | 0x80000000u);
            const unsigned long long k = ((unsigned long long)u << 32) | (uint32_t)(~(tid * 4 + j));
            if (k > b1) { b2 = b1; b1 = k; } else if (k > b2) b2 = k;
        }
    }
    auto merge = [&](int o) {
        const unsigned long long c1 = __shfl_xor_sync(~0u, b1, o), c2 = __shfl_xor_sync(~0u, b2, o);
        const unsigned long long hi = b1 > c1 ? b1 : c1, lo = b1 > c1 ? c1 : b1, s2 = b2 > c2 ? b2 : c2;
        b1 = hi; b2 = lo > s2 ? lo : s2;
    };
    for (int o = 16; o; o >>= 1) merge(o);
    unsigned long long* red = (unsigned long long*)(smem + OFF_MISC + 512);
    if (lane == 0) { red[warp * 2] = b1; red[warp * 2 + 1] = b2; }
    __syncthreads();
    b1 = red[(lane & 15) * 2]; b2 = red[(lane & 15) * 2 + 1];
    for (int o = 8; o; o >>= 1) merge(o);
    const int i0 = (int)(~(uint32_t)b1), i1 = (int)(~(uint32_t)b2);
    if (tid < 128) {
        const int t = tid >> 6, kc = tid & 63;
        *(uint4*)(smem + OFF_XSEL + kc * 128 + t * 16) = *(const uint4*)(P.x + (t ? i1 : i0) * D_ + kc * 8);
    }
    if (part == 0 && tid == 0) {
        g_sel[0] = i0; g_sel[1] = i1;
        g_sel[2] = __float_as_int(rbf(sigmoidf_(g_r[i0])));
        g_sel[3] = __float_as_int(rbf(sigmoidf_(g_r[i1])));
    }
    fence_async_s();
    __syncthreads();
    if (wg == 3) {
        if (tid == 384)
            for (int i = M_STAGES; i < NBOX; i++) {
                mbar_wait(bars + 8 * (B_EMPTY + i % M_STAGES), (i / M_STAGES - 1) & 1);
                issue(i);
            }
    } else if (wg == 0) {
        const int w4 = warp & 3, g = lane >> 2;
        auto box = [&](float (&acc)[4], int i, int nk, uint32_t boff, int first) {
            const int st = i % M_STAGES;
            mbar_wait(bars + 8 * (B_FULL + st), (i / M_STAGES) & 1);
            const uint64_t da = mkdesc(0, 8192, 1024, 1) + st * (M_STAGE_BYTES >> 4), db = mkdesc(0, 128, 256, 0) + (boff >> 4);
            reg_fence(acc);
            wg_fence();
            for (int k = 0; k < nk; k++) wg_ss_n8_at(acc, da + k * 128, db + k * 16, !(first && k == 0));
            wg_commit();
            wg_wait<0>();
            reg_fence(acc);
            if ((tid & 127) == 0) mbar_arrive(bars + 8 * (B_EMPTY + st));
        };
#pragma unroll 1
        for (int j = 0; j < 7; j++) {
            float ag[4] = {0, 0, 0, 0}, au[4] = {0, 0, 0, 0};
            box(ag, 4 * j, 16, OFF_XSEL, 1); box(ag, 4 * j + 1, 16, OFF_XSEL + 4096, 0);
            box(au, 4 * j + 2, 16, OFF_XSEL, 1); box(au, 4 * j + 3, 16, OFF_XSEL + 4096, 0);
            if ((lane & 3) == 0) {
#pragma unroll
                for (int e = 0; e < 4; e++) {
                    const float gv = rbf(ag[e]), h = rbf(gv * sigmoidf_(gv)) * rbf(au[e]);
                    const int f = j * 64 + w4 * 16 + (e >> 1) * 8 + g;
                    *(__nv_bfloat16*)(smem + OFF_HSEL + (f >> 3) * 128 + (e & 1) * 16 + (f & 7) * 2) = __float2bfloat16_rn(h);
                }
            }
        }
        fence_async_s();
        named_sync(1, 128);
#pragma unroll 1
        for (int j = 0; j < 8; j++) {
            float a[4] = {0, 0, 0, 0};
            box(a, 28 + 2 * j, 14, OFF_HSEL, 1); box(a, 29 + 2 * j, 14, OFF_HSEL + 14 * 256, 0);
            if ((lane & 3) == 0) {
#pragma unroll
                for (int e = 0; e < 4; e++) g_y[(part * 2 + (e & 1)) * D_ + j * 64 + w4 * 16 + (e >> 1) * 8 + g] = a[e];
            }
        }
    }
    __syncthreads();
    if (tid == 0) cnt_arrive(13);
}

__global__ void __launch_bounds__(512, 1)
fused_kernel(const __grid_constant__ CUtensorMap mx, const __grid_constant__ CUtensorMap mw, const __grid_constant__ CUtensorMap mo,
             const __grid_constant__ CUtensorMap mg, const __grid_constant__ CUtensorMap mu, const __grid_constant__ CUtensorMap md,
             const __grid_constant__ Params P) {
    extern __shared__ __align__(1024) uint8_t smem[];
    const uint32_t sb = (uint32_t)__cvta_generic_to_shared(smem);
    const int tid = threadIdx.x, lane = tid & 31, warp = tid >> 5, wg = tid >> 7, w4 = warp & 3;
    const int cta = blockIdx.x;
    const uint32_t bars = sb + OFF_MISC;
    volatile uint32_t* misc = (volatile uint32_t*)(smem + OFF_MISC + 256);
    const int nt = cta >> 4, mt = cta & 15;

    if (tid == 256) {
        TSTAMP(0);
        if ((sb & 0x3ffff) != SBASE) __trap();
        for (int i = 0; i < NBAR; i++) mbar_init(bars + 8 * i, (i >= B_EMPTY && i < B_KV && cta < 128) ? 2 : 1);
        asm volatile("fence.mbarrier_init.release.cluster;" ::: "memory");
        fence_async_s();
        if (cta < 128 && (P.mode & 1)) {
            for (int kc = 0; kc < A_STAGES; kc++) {
                const uint32_t bar = bars + 8 * (B_FULL + kc), dst = sb + kc * A_STAGE_BYTES;
                mbar_expect(bar, A_STAGE_BYTES);
                tma2d(dst, &mx, kc * 64, mt * 128, bar);
                for (int j = 0; j < 3; j++) tma2d(dst + 16384 + j * 8192, &mw, j * 512 + nt * 64, kc * 64, bar);
            }
        }
    }
    if (tid == 0) misc[0] = g_epoch[cta] + 1;
    __syncthreads();
    const uint32_t ep = misc[0];
    if (cta >= 128) {
        if (P.mode & 2) mod_cta(smem, sb, P, &mg, &mu, &md, ep);
        if (tid == 0) { TSTAMP(1); if (P.mode & 4) g_epoch[cta] = ep; }
        return;
    }

    if (P.mode & 1) {
        if (wg < 2) {
            float acc[96];
#pragma unroll
            for (int kc = 0; kc < 8; kc++) {
                const int st = kc % A_STAGES;
                mbar_wait(bars + 8 * (B_FULL + st), kc / A_STAGES);
                if (kc == 0 && tid == 0) TSTAMP(1);
                const uint64_t da = mkdesc(st * A_STAGE_BYTES, 16, 1024, 1) + wg * 512;
                const uint64_t db = mkdesc(st * A_STAGE_BYTES + 16384, 8192, 1024, 1);
                wg_fence();
#pragma unroll
                for (int kk = 0; kk < 4; kk++) wg_ss_n192_bt(acc, da + kk * 2, db + kk * 128, kc + kk > 0);
                wg_commit();
                if (kc >= 1 && kc - 1 + A_STAGES < 8) {
                    wg_wait<1>();
                    if ((tid & 127) == 0) mbar_arrive(bars + 8 * (B_EMPTY + kc - 1));
                }
            }
            wg_wait<0>();
            reg_fence(acc);
            if (tid == 0) TSTAMP(2);
            float4* xch = (float4*)(smem + OFF_XCH);
#pragma unroll
            for (int i = 0; i < 4; i++) xch[(warp * 4 + i) * 32 + lane] = make_float4(acc[32 + 8 * i + 2], acc[32 + 8 * i + 3], acc[32 + 8 * i + 6], acc[32 + 8 * i + 7]);
            const int b0 = (mt >> 3) * 16 + 2 * warp, cg = mt & 7;
#pragma unroll
            for (int j = 0; j < 8; j++)
#pragma unroll
                for (int h = 0; h < 2; h++) {
                    uint32_t v = pack_b2(acc[64 + 4 * j + 2 * h], acc[64 + 4 * j + 2 * h + 1]), vt;
                    asm volatile("movmatrix.sync.aligned.m8n8.trans.b16 %0, %1;" : "=r"(vt) : "r"(v));
                    const int ch = 4 * (b0 + h) + (cg >> 1);
                    const int off = (j & 1) ? 32768 + 256 * ch : 32768 - 256 * (ch + 1);
                    *(uint32_t*)(g_v + (nt * 4 + (j >> 1)) * 65536 + off + (cg & 1) * 128 + lane * 4) = vt;
                }
#pragma unroll
            for (int hh = 0; hh < 4; hh++)
                g_q[((nt * 4 + hh) * 32 + mt * 2 + wg) * 128 + (tid & 127)] =
                    make_uint4(pack_h2(acc[8 * hh] * QSCALE, acc[8 * hh + 1] * QSCALE), pack_h2(acc[8 * hh + 2] * QSCALE, acc[8 * hh + 3] * QSCALE),
                               pack_h2(acc[8 * hh + 4] * QSCALE, acc[8 * hh + 5] * QSCALE), pack_h2(acc[8 * hh + 6] * QSCALE, acc[8 * hh + 7] * QSCALE));
            named_sync(1, 256);
            float cs = 1.f;
#pragma unroll
            for (int c = 0; c < 8; c++) if (cg_scaled(c) && cg == c) cs = 0.5f;
            float nrm[8];
#pragma unroll
            for (int hh = 0; hh < 4; hh++) {
                float4 pv = make_float4(0.f, 0.f, 0.f, 0.f);
                if (warp > 0) pv = xch[((warp - 1) * 4 + hh) * 32 + lane];
                const float* k = &acc[32 + 8 * hh];
                uint32_t* dst = (uint32_t*)(g_k + (nt * 4 + hh) * 65536 + b0 * 2048 + cg * 256) + lane;
                dst[0] = pack_h2((k[0] - pv.x) * cs, (k[1] - pv.y) * cs);
                dst[32] = pack_h2((k[4] - pv.z) * cs, (k[5] - pv.w) * cs);
                dst[512] = pack_h2((k[2] - k[0]) * cs, (k[3] - k[1]) * cs);
                dst[544] = pack_h2((k[6] - k[4]) * cs, (k[7] - k[5]) * cs);
                nrm[2 * hh] = k[0] * k[0] + k[1] * k[1] + k[4] * k[4] + k[5] * k[5];
                nrm[2 * hh + 1] = k[2] * k[2] + k[3] * k[3] + k[6] * k[6] + k[7] * k[7];
            }
            {
                const bool o2 = lane & 2, o1 = lane & 1;
                float u[4];
#pragma unroll
                for (int i = 0; i < 4; i++) u[i] = (o2 ? nrm[4 + i] : nrm[i]) + __shfl_xor_sync(~0u, o2 ? nrm[i] : nrm[4 + i], 2);
                const float a = (o1 ? u[2] : u[0]) + __shfl_xor_sync(~0u, o1 ? u[0] : u[2], 1);
                const float b = (o1 ? u[3] : u[1]) + __shfl_xor_sync(~0u, o1 ? u[1] : u[3], 1);
                uint32_t m = max(__float_as_uint(a), __float_as_uint(b));
                m = max(m, __shfl_xor_sync(~0u, m, 4));
                m = max(m, __shfl_xor_sync(~0u, m, 8));
                m = max(m, __shfl_xor_sync(~0u, m, 16));
                if (lane < 4) g_kmax[(nt * 4 + lane) * 128 + mt * 8 + warp] = __uint_as_float(m);
            }
        } else if (wg == 2) {
            if (tid == 256)
                for (int kc = A_STAGES; kc < 8; kc++) {
                    const int st = kc - A_STAGES;
                    const uint32_t bar = bars + 8 * (B_FULL + st), dst = sb + st * A_STAGE_BYTES;
                    mbar_wait(bars + 8 * (B_EMPTY + st), 0);
                    mbar_expect(bar, A_STAGE_BYTES);
                    tma2d(dst, &mx, kc * 64, mt * 128, bar);
                    for (int j = 0; j < 3; j++) tma2d(dst + 16384 + j * 8192, &mw, j * 512 + nt * 64, kc * 64, bar);
                }
        } else {
            const int row0 = mt * 128 + nt * 16 + w4 * 4;
            uint4 xv[4][2], wr[2], wgt[2];
#pragma unroll
            for (int c = 0; c < 2; c++) {
#pragma unroll
                for (int r = 0; r < 4; r++) xv[r][c] = *(const uint4*)(P.x + (row0 + r) * D_ + c * 256 + lane * 8);
                wr[c] = *(const uint4*)(P.w_r + c * 256 + lane * 8);
                wgt[c] = *(const uint4*)(P.gate_w + c * 256 + lane * 8);
            }
            auto dot8 = [](uint4 a, uint4 b) {
                return blo(a.x) * blo(b.x) + bhi(a.x) * bhi(b.x) + blo(a.y) * blo(b.y) + bhi(a.y) * bhi(b.y) +
                       blo(a.z) * blo(b.z) + bhi(a.z) * bhi(b.z) + blo(a.w) * blo(b.w) + bhi(a.w) * bhi(b.w);
            };
#pragma unroll
            for (int r = 0; r < 4; r++) {
                float a = dot8(xv[r][0], wr[0]) + dot8(xv[r][1], wr[1]), b = dot8(xv[r][0], wgt[0]) + dot8(xv[r][1], wgt[1]);
#pragma unroll
                for (int o = 16; o; o >>= 1) { a += __shfl_xor_sync(~0u, a, o); b += __shfl_xor_sync(~0u, b, o); }
                if (lane == 0) { g_r[row0 + r] = rbf(a); g_g[row0 + r] = sigmoidf_(b); }
            }
            named_sync(2, 128);
            if (tid == 384) cnt_arrive(12);
        }
        fence_async_g();
        fence_async_s();
        __syncthreads();
        if (tid == 0) { cnt_arrive(nt); TSTAMP(3); }
    }

    const int head = nt * 4 + (mt & 3), rg = mt >> 2;
    const int ct = mt & 3, rt = rg * 8 + nt;
    auto load_wo = [&](int kc0, int kc1, int off, int bi) {
        mbar_expect(bars + 8 * bi, (kc1 - kc0) * 16384);
        for (int kc = kc0; kc < kc1; kc++)
            for (int j = 0; j < 2; j++) tma2d(sb + off + ((kc - kc0) * 2 + j) * 8192, &mo, ct * 128 + j * 64, kc * 64, bars + 8 * bi);
    };
    if (P.mode & 2) {
        if (tid < 64) ((uint32_t*)(smem + OFF_ONE))[tid] = 0x3f803f80u;
        if (tid == 0) {
            cnt_wait(nt, 16 * ep);
            TSTAMP(4);
            fence_async_g();
            const uint8_t *kp = g_k + head * 65536, *vp = g_v + head * 65536 + 32768;
            for (int st = 0; st < 8; st++) {
                const uint32_t bar = bars + 8 * (B_KV + st);
                mbar_expect(bar, 16384);
                bulk_ld(sb + OFF_K + st * 8192, kp + st * 8192, 8192, bar);
                bulk_ld(sb + OFF_ONE - (st + 1) * 4096, vp - (st + 1) * 4096, 4096, bar);
                bulk_ld(sb + OFF_VHI + st * 4096, vp + st * 4096, 4096, bar);
            }
        }
        fence_async_s();
        __syncthreads();
        const uint4 qa = g_q[(head * 32 + rg * 8 + wg) * 128 + (tid & 127)], qb = g_q[(head * 32 + rg * 8 + 4 + wg) * 128 + (tid & 127)];
        const uint4 kmv = *(const uint4*)(g_kmax + head * 128 + lane * 4);
        if (tid == 32 && (P.mode & 4)) load_wo(0, 6, OFF_WO1, B_WO1);
        const float kmax2 = __uint_as_float(__reduce_max_sync(~0u, max(max(kmv.x, kmv.y), max(kmv.z, kmv.w))));
        auto sq = [](uint32_t a, uint32_t b) {
            const float2 u = __half22float2(*(const __half2*)&a), v = __half22float2(*(const __half2*)&b);
            float n = u.x * u.x + u.y * u.y + v.x * v.x + v.y * v.y;
            n += __shfl_xor_sync(~0u, n, 1);
            return n + __shfl_xor_sync(~0u, n, 2);
        };
        const float n0 = sq(qa.x, qa.z), n1 = sq(qa.y, qa.w), n2 = sq(qb.x, qb.z), n3 = sq(qb.y, qb.w);
        const float lim = BOUND_MAX * BOUND_MAX;
        const bool ok = n0 * kmax2 <= lim && n1 * kmax2 <= lim && n2 * kmax2 <= lim && n3 * kmax2 <= lim &&
                        kmax2 <= 65536.f && n0 + n1 + n2 + n3 <= 65536.f;
        if (__syncthreads_and(ok)) {
            float s[32], o[12];
            uint32_t p[16];
            uint32_t q0 = qa.x, q1 = qa.y, q2 = qa.z, q3 = qa.w;
            uint32_t c7f = 0x007f007fu;
            asm volatile("" : "+r"(c7f));
            constexpr uint64_t dk0 = mkdesc(OFF_K, 128, 256, 0), dv0 = mkdesc(OFF_ONE - 256, 128, 256, 0);
            InitLoop<0>::run(s);
#pragma unroll
            for (int i = 0; i < 12; i++) o[i] = 0.f;
            reg_fence(s);
            reg_fence(o);
            mbar_wait(bars + 8 * B_KV, 0);
            if (tid == 0) TSTAMP(5);
            wg_fence();
            wg_rs_qk(s, q0, q1, q2, q3, dk0);
            wg_commit();
#pragma unroll 1
            for (int seg = 0; seg < 4; seg++) {
                uint64_t dk = dk0 + (seg & 1) * 2048, dv = dv0 + (seg & 1) * (64 * DV_STEP);
                uint32_t nb = bars + 8 * (B_KV + 1 + (seg & 1) * 4);
#pragma unroll 1
                for (int it = 0; it < 3; it++, dk += 512, dv += 16 * DV_STEP, nb += 8) {
#pragma unroll
                    for (int u = 0; u < 4; u++) {
                        wg_wait<0>();
                        reg_fence(s);
                        ExpLoop<0>::run(s, p, c7f);
                        if (u == 3) mbar_wait(nb, 0);
                        wg_fence();
                        wg_rs_qk(s, q0, q1, q2, q3, dk + (u + 1) * 128);
#pragma unroll
                        for (int j = 0; j < 4; j++) wg_rs_pv(o, p[4 * j], p[4 * j + 1], p[4 * j + 2], p[4 * j + 3], dv + (4 * u + j) * DV_STEP);
                        wg_commit();
                    }
                }
#pragma unroll
                for (int u = 0; u < 4; u++) {
                    wg_wait<0>();
                    reg_fence(s);
                    ExpLoop<0>::run(s, p, c7f);
                    uint64_t dn = dk + (u + 1) * 128;
                    if (u == 3) {
                        InitLoop<0>::run(s);
                        reg_fence(s);
                        if (seg & 1) { q0 = qb.x; q1 = qb.y; q2 = qb.z; q3 = qb.w; dn = dk0; }
                        else mbar_wait(nb, 0);
                    }
                    wg_fence();
                    wg_rs_qk(s, q0, q1, q2, q3, dn);
#pragma unroll
                    for (int j = 0; j < 4; j++) wg_rs_pv(o, p[4 * j], p[4 * j + 1], p[4 * j + 2], p[4 * j + 3], dv + (4 * u + j) * DV_STEP);
                    wg_commit();
                }
                if (seg & 1) {
                    wg_wait<0>();
                    reg_fence(o);
                    store_o(o, rg * 8 + (seg >> 1) * 4 + wg, head, w4, lane);
#pragma unroll
                    for (int i = 0; i < 12; i++) o[i] = 0.f;
                    reg_fence(o);
                }
            }
            wg_wait<0>();
            reg_fence(s);
        } else {
            for (int st = 0; st < 8; st++) mbar_wait(bars + 8 * (B_KV + st), 0);
            attn_slow(smem, P.x, P.wqkv, head, rg);
        }
        if (tid == 0) TSTAMP(6);
        fence_async_g();
        fence_async_s();
        __syncthreads();
        if (tid == 0) { cnt_arrive(8 + rg); TSTAMP(7); }
    }

    if (P.mode & 4) {
        if (tid == 256) {
            if (!(P.mode & 2)) load_wo(0, 6, OFF_WO1, B_WO1);
            load_wo(6, 8, OFF_WO2, B_WO2);
            cnt_wait(8 + rg, 32 * ep);
            TSTAMP(8);
            fence_async_g();
            for (int c = 0; c < 4; c++) {
                mbar_expect(bars + 8 * (B_O + c), 16384);
                bulk_ld(sb + OFF_O + c * 16384, g_o + rt * 65536 + c * 16384, 16384, bars + 8 * (B_O + c));
            }
        }
        if (wg < 2) {
            if (lane == 0) { cnt_wait(13, 4 * ep); cnt_wait(12, 128 * ep); }
            __syncwarp();
            const int row = rt * 64 + w4 * 16 + (lane >> 2), col = ct * 128 + wg * 64 + (lane & 3) * 2;
            uint32_t xr[16];
#pragma unroll
            for (int j = 0; j < 8; j++) {
                xr[2 * j] = *(const uint32_t*)(P.x + row * D_ + col + j * 8);
                xr[2 * j + 1] = *(const uint32_t*)(P.x + (row + 8) * D_ + col + j * 8);
            }
            const float g0 = __ldcg(g_g + row), g1 = __ldcg(g_g + row + 8);
            const int4 sel = __ldcg((const int4*)g_sel);
#pragma unroll
            for (int h = 0; h < 2; h++) {
                const int r = row + 8 * h;
                if (r == sel.x || r == sel.y) {
                    const int t = r == sel.x ? 0 : 1;
                    const float rs = __int_as_float(t ? sel.w : sel.z);
#pragma unroll
                    for (int j = 0; j < 8; j++) {
                        float y0 = 0.f, y1 = 0.f;
                        for (int pp = 0; pp < 4; pp++) {
                            const float2 v = __ldcg((const float2*)(g_y + (pp * 2 + t) * D_ + col + j * 8));
                            y0 += v.x; y1 += v.y;
                        }
                        xr[2 * j + h] = pack_b2(blo(xr[2 * j + h]) + rbf(rbf(y0) * rs), bhi(xr[2 * j + h]) + rbf(rbf(y1) * rs));
                    }
                }
            }
            __syncwarp();
            float acc[32];
            mbar_wait(bars + 8 * B_WO1, 0);
#pragma unroll
            for (int c = 0; c < 4; c++) {
                if (c == 3) mbar_wait(bars + 8 * B_WO2, 0);
                mbar_wait(bars + 8 * (B_O + c), 0);
                if (c == 0 && tid == 0) TSTAMP(9);
                wg_fence();
#pragma unroll
                for (int k = 0; k < 8; k++) {
                    const int kc = c * 2 + (k >> 2);
                    const uint64_t da = mkdesc(OFF_O + (c * 8 + k) * 2048, 128, 256, 0);
                    const uint64_t db = mkdesc((kc < 6 ? OFF_WO1 + kc * 16384 : OFF_WO2 + (kc - 6) * 16384) + (k & 3) * 2048, 8192, 1024, 1) + wg * 512;
                    wg_ss_n64_bt(acc, da, db, c + k > 0);
                }
                wg_commit();
            }
            wg_wait<0>();
            reg_fence(acc);
            if (tid == 0) TSTAMP(10);
#pragma unroll
            for (int j = 0; j < 8; j++) {
                *(uint32_t*)(P.out + row * D_ + col + j * 8) =
                    pack_b2(g0 * acc[4 * j] + (1.f - g0) * blo(xr[2 * j]), g0 * acc[4 * j + 1] + (1.f - g0) * bhi(xr[2 * j]));
                *(uint32_t*)(P.out + (row + 8) * D_ + col + j * 8) =
                    pack_b2(g1 * acc[4 * j + 2] + (1.f - g1) * blo(xr[2 * j + 1]), g1 * acc[4 * j + 3] + (1.f - g1) * bhi(xr[2 * j + 1]));
            }
            if (tid == 0) { g_epoch[cta] = ep; TSTAMP(11); }
        }
    }
}

typedef CUresult (*EncodeFn)(CUtensorMap*, CUtensorMapDataType, cuuint32_t, void*, const cuuint64_t*, const cuuint64_t*, const cuuint32_t*,
                             const cuuint32_t*, CUtensorMapInterleave, CUtensorMapSwizzle, CUtensorMapL2promotion, CUtensorMapFloatOOBfill);

void make_map(EncodeFn fn, CUtensorMap* m, const void* p, int rows, int cols, int box_rows) {
    cuuint64_t dims[2] = {(cuuint64_t)cols, (cuuint64_t)rows}, strides[1] = {(cuuint64_t)cols * 2};
    cuuint32_t box[2] = {64, (cuuint32_t)box_rows}, es[2] = {1, 1};
    fn(m, CU_TENSOR_MAP_DATA_TYPE_BFLOAT16, 2, (void*)p, dims, strides, box, es, CU_TENSOR_MAP_INTERLEAVE_NONE, CU_TENSOR_MAP_SWIZZLE_128B,
       CU_TENSOR_MAP_L2_PROMOTION_L2_128B, CU_TENSOR_MAP_FLOAT_OOB_FILL_NONE);
}

}

extern "C" void kernel_launch(void* const* d_in, const int* in_sizes, int n_in, void* d_out, int out_size) {
    static EncodeFn fn = nullptr;
    static int resident = 0;
    if (!fn) {
        void* f = nullptr;
        cudaDriverEntryPointQueryResult qr;
        cudaGetDriverEntryPoint("cuTensorMapEncodeTiled", &f, cudaEnableDefault, &qr);
        fn = (EncodeFn)f;
        cudaFuncSetAttribute(fused_kernel, cudaFuncAttributeMaxDynamicSharedMemorySize, SMEM_BYTES);
        int dev = 0, sms = 0, per = 0;
        cudaGetDevice(&dev);
        cudaDeviceGetAttribute(&sms, cudaDevAttrMultiProcessorCount, dev);
        cudaOccupancyMaxActiveBlocksPerMultiprocessor(&per, fused_kernel, 512, SMEM_BYTES);
        resident = sms * per;
    }
    CUtensorMap mx, mw, mo, mg, mu, md;
    make_map(fn, &mx, d_in[0], S_, D_, 128);
    make_map(fn, &mw, d_in[1], D_, 3 * D_, 64);
    make_map(fn, &mo, d_in[2], D_, D_, 64);
    make_map(fn, &mg, d_in[5], D_, F_, 256);
    make_map(fn, &mu, d_in[6], D_, F_, 256);
    make_map(fn, &md, d_in[7], F_, D_, 224);
    Params P;
    P.x = (const __nv_bfloat16*)d_in[0];
    P.wqkv = (const __nv_bfloat16*)d_in[1];
    P.w_r = (const __nv_bfloat16*)d_in[4];
    P.gate_w = (const __nv_bfloat16*)d_in[8];
    P.out = (__nv_bfloat16*)d_out;
    if (resident >= NCTA) {
        P.mode = 7;
        fused_kernel<<<NCTA, 512, SMEM_BYTES, cudaStreamPerThread>>>(mx, mw, mo, mg, mu, md, P);
    } else {
        for (int ph = 1; ph <= 4; ph <<= 1) {
            P.mode = ph;
            fused_kernel<<<NCTA, 512, SMEM_BYTES, cudaStreamPerThread>>>(mx, mw, mo, mg, mu, md, P);
        }
    }
}
```

```cpp
#include <cuda_runtime.h>
#include <cuda_bf16.h>
#include <cuda_fp16.h>
#include <cuda.h>
#include <stdint.h>

namespace {

constexpr int S_ = 2048, D_ = 512, F_ = 1792;
constexpr int NCTA = 132, NTHR = 640;
constexpr uint32_t SBASE = 0x400;
constexpr int SMEM_BYTES = 232448;

__host__ __device__ constexpr int off_w(int i) { return i == 0 ? 0 : 2048 + i * 16384; }
__host__ __device__ constexpr int off_x(int c) { return 100352 + (7 - c) * 16384; }
constexpr int SLOT = 34816;
constexpr int OFF_WOE = 4 * SLOT;
constexpr int OFF_STG = OFF_WOE + 65536;
constexpr int OFF_MISC = 231424;
constexpr int M_STAGES = 6, M_STAGE_BYTES = 32768;
constexpr int OFF_XSEL = M_STAGES * M_STAGE_BYTES, OFF_HSEL = OFF_XSEL + 8192;
constexpr int B_AF = 0, B_AE = 8, B_QF = 14, B_AFREE = 18, B_KVP = 19, B_KF = 20, B_WL = 24, B_WOE = 26, B_OP = 28, B_OL = 30, B_MX = 34;
constexpr unsigned long long BAR_CNT = 0x00700f0044700111ull;
constexpr int C_KV = 0, C_O = 8, C_R = 40, C_Y = 41, C_MX = 42, NCNT = 50;

#define EXP_PAT 0x3333303033333030ull
constexpr unsigned long long PAT = EXP_PAT;
__host__ __device__ constexpr int pat_of(int i) { return (int)((PAT >> (4 * i)) & 15); }
constexpr float U0 = 14.f, OFF_C = 1.585497f, OFF_E = 2.083684f;
__host__ __device__ constexpr float init_of(int i) {
    return pat_of(i) == 0 ? U0 - 15.f + OFF_E : pat_of(i) == 2 ? 32.f + U0 + OFF_E - OFF_C : 32.f + U0;
}
#define ARR 0
constexpr float BOUND_MAX = 17.2f;
constexpr float QSCALE = 0.25f * 1.4426950408889634f;

__device__ __align__(1024) uint8_t g_kv[8 * 2 * 8 * 32768];
__device__ __align__(1024) uint8_t g_o[32 * 65536];
__device__ __align__(16) float g_mx[8 * 128];
__device__ __align__(16) float g_r[S_];
__device__ __align__(16) float g_g[S_];
__device__ __align__(16) float g_y[4 * 2 * D_];
__device__ __align__(16) int g_sel[4];
__device__ uint32_t g_cnt[NCNT * 32];
__device__ uint32_t g_epoch[NCTA];
#define TSTAMP(i)
#define CSTAMP(i)

__device__ __forceinline__ void wg_ss_n128_at(float (&d)[64], uint64_t da, uint64_t db, int acc) {
  asm volatile("{\n.reg .pred p;\nsetp.ne.b32 p, %66, 0;\n"
      "wgmma.mma_async.sync.aligned.m64n128k16.f32.bf16.bf16 {%0,%1,%2,%3,%4,%5,%6,%7,%8,%9,%10,%11,%12,%13,%14,%15,%16,%17,%18,%19,%20,%21,%22,%23,"
      "%24,%25,%26,%27,%28,%29,%30,%31,%32,%33,%34,%35,%36,%37,%38,%39,%40,%41,%42,%43,%44,%45,%46,%47,"
      "%48,%49,%50,%51,%52,%53,%54,%55,%56,%57,%58,%59,%60,%61,%62,%63}, %64, %65, p, 1, 1, 1, 0;\n}\n"
    : "+f"(d[0]), "+f"(d[1]), "+f"(d[2]), "+f"(d[3]), "+f"(d[4]), "+f"(d[5]), "+f"(d[6]), "+f"(d[7]), "+f"(d[8]), "+f"(d[9]), "+f"(d[10]), "+f"(d[11]),
      "+f"(d[12]), "+f"(d[13]), "+f"(d[14]), "+f"(d[15]), "+f"(d[16]), "+f"(d[17]), "+f"(d[18]), "+f"(d[19]), "+f"(d[20]), "+f"(d[21]), "+f"(d[22]), "+f"(d[23]),
      "+f"(d[24]), "+f"(d[25]), "+f"(d[26]), "+f"(d[27]), "+f"(d[28]), "+f"(d[29]), "+f"(d[30]), "+f"(d[31]), "+f"(d[32]), "+f"(d[33]), "+f"(d[34]), "+f"(d[35]),
      "+f"(d[36]), "+f"(d[37]), "+f"(d[38]), "+f"(d[39]), "+f"(d[40]), "+f"(d[41]), "+f"(d[42]), "+f"(d[43]), "+f"(d[44]), "+f"(d[45]), "+f"(d[46]), "+f"(d[47]),
      "+f"(d[48]), "+f"(d[49]), "+f"(d[50]), "+f"(d[51]), "+f"(d[52]), "+f"(d[53]), "+f"(d[54]), "+f"(d[55]), "+f"(d[56]), "+f"(d[57]), "+f"(d[58]), "+f"(d[59]),
      "+f"(d[60]), "+f"(d[61]), "+f"(d[62]), "+f"(d[63])
    : "l"(da), "l"(db), "r"(acc));
}
__device__ __forceinline__ void wg_ss_n64_bt(float (&d)[32], uint64_t da, uint64_t db, int acc) {
  asm volatile("{\n.reg .pred p;\nsetp.ne.b32 p, %34, 0;\n"
      "wgmma.mma_async.sync.aligned.m64n64k16.f32.bf16.bf16 {%0,%1,%2,%3,%4,%5,%6,%7,%8,%9,%10,%11,%12,%13,%14,%15,%16,%17,%18,%19,%20,%21,%22,%23,"
      "%24,%25,%26,%27,%28,%29,%30,%31}, %32, %33, p, 1, 1, 0, 1;\n}\n"
    : "+f"(d[0]), "+f"(d[1]), "+f"(d[2]), "+f"(d[3]), "+f"(d[4]), "+f"(d[5]), "+f"(d[6]), "+f"(d[7]), "+f"(d[8]), "+f"(d[9]), "+f"(d[10]), "+f"(d[11]),
      "+f"(d[12]), "+f"(d[13]), "+f"(d[14]), "+f"(d[15]), "+f"(d[16]), "+f"(d[17]), "+f"(d[18]), "+f"(d[19]), "+f"(d[20]), "+f"(d[21]), "+f"(d[22]), "+f"(d[23]),
      "+f"(d[24]), "+f"(d[25]), "+f"(d[26]), "+f"(d[27]), "+f"(d[28]), "+f"(d[29]), "+f"(d[30]), "+f"(d[31])
    : "l"(da), "l"(db), "r"(acc));
}
__device__ __forceinline__ void wg_ss_n8_at(float (&d)[4], uint64_t da, uint64_t db, int acc) {
  asm volatile("{\n.reg .pred p;\nsetp.ne.b32 p, %6, 0;\n"
      "wgmma.mma_async.sync.aligned.m64n8k16.f32.bf16.bf16 {%0,%1,%2,%3}, %4, %5, p, 1, 1, 1, 0;\n}\n"
    : "+f"(d[0]), "+f"(d[1]), "+f"(d[2]), "+f"(d[3])
    : "l"(da), "l"(db), "r"(acc));
}
__device__ __forceinline__ void wg_rs_qk(float (&d)[32], uint32_t a0, uint32_t a1, uint32_t a2, uint32_t a3, uint64_t db) {
  asm volatile("wgmma.mma_async.sync.aligned.m64n64k16.f32.f16.f16 {%0,%1,%2,%3,%4,%5,%6,%7,%8,%9,%10,%11,%12,%13,%14,%15,%16,%17,%18,%19,%20,%21,%22,%23,"
      "%24,%25,%26,%27,%28,%29,%30,%31}, {%32,%33,%34,%35}, %36, 1, 1, 1, 1;\n"
    : "+f"(d[0]), "+f"(d[1]), "+f"(d[2]), "+f"(d[3]), "+f"(d[4]), "+f"(d[5]), "+f"(d[6]), "+f"(d[7]), "+f"(d[8]), "+f"(d[9]), "+f"(d[10]), "+f"(d[11]),
      "+f"(d[12]), "+f"(d[13]), "+f"(d[14]), "+f"(d[15]), "+f"(d[16]), "+f"(d[17]), "+f"(d[18]), "+f"(d[19]), "+f"(d[20]), "+f"(d[21]), "+f"(d[22]), "+f"(d[23]),
      "+f"(d[24]), "+f"(d[25]), "+f"(d[26]), "+f"(d[27]), "+f"(d[28]), "+f"(d[29]), "+f"(d[30]), "+f"(d[31])
    : "r"(a0), "r"(a1), "r"(a2), "r"(a3), "l"(db));
}
__device__ __forceinline__ void wg_rs_pv(uint32_t (&d)[6], uint32_t a0, uint32_t a1, uint32_t a2, uint32_t a3, uint64_t db) {
  asm volatile("wgmma.mma_async.sync.aligned.m64n24k16.f16.f16.f16 {%0,%1,%2,%3,%4,%5}, {%6,%7,%8,%9}, %10, 1, 1, 1, 0;\n"
    : "+r"(d[0]), "+r"(d[1]), "+r"(d[2]), "+r"(d[3]), "+r"(d[4]), "+r"(d[5])
    : "r"(a0), "r"(a1), "r"(a2), "r"(a3), "l"(db));
}
__device__ __forceinline__ void wg_rs_pv0(uint32_t (&d)[6], uint32_t a0, uint32_t a1, uint32_t a2, uint32_t a3, uint64_t db) {
  asm volatile("wgmma.mma_async.sync.aligned.m64n24k16.f16.f16.f16 {%0,%1,%2,%3,%4,%5}, {%6,%7,%8,%9}, %10, 0, 1, 1, 0;\n"
    : "+r"(d[0]), "+r"(d[1]), "+r"(d[2]), "+r"(d[3]), "+r"(d[4]), "+r"(d[5])
    : "r"(a0), "r"(a1), "r"(a2), "r"(a3), "l"(db));
}

__device__ __forceinline__ void wg_fence() { asm volatile("wgmma.fence.sync.aligned;" ::: "memory"); }
__device__ __forceinline__ void wg_commit() { asm volatile("wgmma.commit_group.sync.aligned;" ::: "memory"); }
template <int N> __device__ __forceinline__ void wg_wait() { asm volatile("wgmma.wait_group.sync.aligned %0;" ::"n"(N) : "memory"); }
template <int N> __device__ __forceinline__ void reg_fence(float (&r)[N]) {
#pragma unroll
    for (int i = 0; i < N; i++) asm volatile("" : "+f"(r[i])::"memory");
}
template <int N> __device__ __forceinline__ void reg_fence(uint32_t (&r)[N]) {
#pragma unroll
    for (int i = 0; i < N; i++) asm volatile("" : "+r"(r[i])::"memory");
}
__device__ __forceinline__ void mbar_init(uint32_t bar, int cnt) { asm volatile("mbarrier.init.shared::cta.b64 [%0], %1;" ::"r"(bar), "r"(cnt) : "memory"); }
__device__ __forceinline__ void mbar_expect(uint32_t bar, int bytes) { asm volatile("mbarrier.arrive.expect_tx.shared::cta.b64 _, [%0], %1;" ::"r"(bar), "r"(bytes) : "memory"); }
__device__ __forceinline__ void mbar_arrive(uint32_t bar) { asm volatile("mbarrier.arrive.shared::cta.b64 _, [%0];" ::"r"(bar) : "memory"); }
__device__ __forceinline__ void mbar_wait(uint32_t bar, int parity) {
    asm volatile("{\n.reg .pred p;\n.reg .u32 n;\nmov.u32 n, 0;\n"
                 "W_%=:\nmbarrier.try_wait.parity.shared::cta.b64 p, [%0], %1;\n@p bra D_%=;\n"
                 "add.u32 n, n, 1;\nsetp.lt.u32 p, n, 0x4000000;\n@p bra W_%=;\ntrap;\nD_%=:\n}" ::"r"(bar), "r"(parity) : "memory");
}
__device__ __forceinline__ void mbar_wait_u(uint32_t bar, int parity) {
    for (uint32_t n = 0;; n++) {
        uint32_t ok;
        asm volatile("{\n.reg .pred p;\nmbarrier.try_wait.parity.shared::cta.b64 p, [%1], %2;\nselp.u32 %0, 1, 0, p;\n}" : "=r"(ok) : "r"(bar), "r"(parity) : "memory");
        if (__all_sync(~0u, ok)) break;
        if (n > 0x4000000u) __trap();
    }
}
__device__ __forceinline__ void tma2d(uint32_t dst, const CUtensorMap* m, int c0, int c1, uint32_t bar) {
    asm volatile("cp.async.bulk.tensor.2d.shared::cluster.global.mbarrier::complete_tx::bytes [%0], [%1, {%2, %3}], [%4];"
                 ::"r"(dst), "l"(m), "r"(c0), "r"(c1), "r"(bar) : "memory");
}
__device__ __forceinline__ void tma3d(uint32_t dst, const CUtensorMap* m, int c0, int c1, int c2, uint32_t bar) {
    asm volatile("cp.async.bulk.tensor.3d.shared::cluster.global.mbarrier::complete_tx::bytes [%0], [%1, {%2, %3, %4}], [%5];"
                 ::"r"(dst), "l"(m), "r"(c0), "r"(c1), "r"(c2), "r"(bar) : "memory");
}
__device__ __forceinline__ void tma4d(uint32_t dst, const CUtensorMap* m, int c0, int c1, int c2, int c3, uint32_t bar) {
    asm volatile("cp.async.bulk.tensor.4d.shared::cluster.global.mbarrier::complete_tx::bytes [%0], [%1, {%2, %3, %4, %5}], [%6];"
                 ::"r"(dst), "l"(m), "r"(c0), "r"(c1), "r"(c2), "r"(c3), "r"(bar) : "memory");
}
__device__ __forceinline__ void l2_prefetch(const void* src, int bytes) {
    asm volatile("cp.async.bulk.prefetch.L2.global [%0], %1;" ::"l"(src), "r"(bytes) : "memory");
}
__device__ __forceinline__ void bulk_ld(uint32_t dst, const void* src, int bytes, uint32_t bar) {
    asm volatile("cp.async.bulk.shared::cluster.global.mbarrier::complete_tx::bytes [%0], [%1], %2, [%3];"
                 ::"r"(dst), "l"(src), "r"(bytes), "r"(bar) : "memory");
}
__device__ __forceinline__ void fence_async_s() { asm volatile("fence.proxy.async.shared::cta;" ::: "memory"); }
__device__ __forceinline__ void fence_async_g() { asm volatile("fence.proxy.async.global;" ::: "memory"); }
__device__ __forceinline__ void cnt_arrive(int i) {
    asm volatile("red.release.gpu.global.add.u32 [%0], 1;" ::"l"(&g_cnt[i * 32]) : "memory");
}
__device__ __forceinline__ void cnt_wait(int i, uint32_t target) {
    for (uint32_t n = 0;; n++) {
        uint32_t v;
        asm volatile("ld.acquire.gpu.global.u32 %0, [%1];" : "=r"(v) : "l"(&g_cnt[i * 32]) : "memory");
        if ((int)(v - target) >= 0) break;
        if (n > 0x800000u) __trap();
    }
}
__device__ __forceinline__ void named_sync(int id, int n) { asm volatile("bar.sync %0, %1;" ::"r"(id), "r"(n) : "memory"); }
__device__ __forceinline__ uint32_t pack_h2(float lo, float hi) { uint32_t r; asm("cvt.rn.f16x2.f32 %0, %1, %2;" : "=r"(r) : "f"(hi), "f"(lo)); return r; }
__device__ __forceinline__ uint32_t pack_b2(float lo, float hi) { uint32_t r; asm("cvt.rn.bf16x2.f32 %0, %1, %2;" : "=r"(r) : "f"(hi), "f"(lo)); return r; }
__device__ __forceinline__ float2 h2f(uint32_t v) {
    float2 r;
    asm("{.reg .b16 a, b; mov.b32 {a, b}, %2; cvt.f32.f16 %0, a; cvt.f32.f16 %1, b;}" : "=f"(r.x), "=f"(r.y) : "r"(v));
    return r;
}
__device__ __forceinline__ float blo(uint32_t v) { return __uint_as_float(v << 16); }
__device__ __forceinline__ float bhi(uint32_t v) { return __uint_as_float(v & 0xffff0000u); }
__device__ __forceinline__ float rbf(float v) { return __bfloat162float(__float2bfloat16_rn(v)); }
__device__ __forceinline__ float frcp(float v) { float r; asm("rcp.approx.f32 %0, %1;" : "=f"(r) : "f"(v)); return r; }
__device__ __forceinline__ float sigmoidf_(float v) { return frcp(1.f + __expf(-v)); }
__host__ __device__ constexpr uint64_t mkdesc(uint32_t off, uint32_t lbo, uint32_t sbo, uint32_t swz) {
    return (uint64_t)((SBASE + off) >> 4) | ((uint64_t)(lbo >> 4) << 16) | ((uint64_t)(sbo >> 4) << 32) | ((uint64_t)swz << 62);
}

template <int T> __device__ __forceinline__ uint32_t exp_pair(float a, float b, uint32_t c3c) {
    uint32_t r;
    if (T == 0) {
        float x, y;
        asm("ex2.approx.ftz.f32 %0, %1;" : "=f"(x) : "f"(a));
        asm("ex2.approx.ftz.f32 %0, %1;" : "=f"(y) : "f"(b));
        r = pack_h2(x, y);
    } else {
        uint32_t y;
        asm("prmt.b32 %0, %1, %2, 0x6521;" : "=r"(y) : "r"(__float_as_uint(a)), "r"(__float_as_uint(b)));
        if (T == 2) {
            uint32_t m, e = y | 0x03ff03ffu;
            asm("lop3.b32 %0, %1, 0x03ff03ff, %2, 0xea;" : "=r"(m) : "r"(y), "r"(c3c));
            asm("fma.rn.relu.f16x2 %0, %1, %2, %3;" : "=r"(r) : "r"(y), "r"(m), "r"(e));
        } else {
            uint32_t z = 0xfbdafbdau - y, w;
            asm("{.reg .b32 c; mov.b32 c, 0x45304530; fma.rn.f16x2 %0, %1, %2, c;}" : "=r"(w) : "r"(y), "r"(z));
            asm("fma.rn.relu.f16x2 %0, %1, %2, %1;" : "=r"(r) : "r"(y), "r"(w));
        }
    }
    return r;
}
template <int I> struct ExpLoop {
    static __device__ __forceinline__ void run(float (&s)[32], uint32_t (&p)[16], uint32_t c3c) {
        p[I] = exp_pair<pat_of(I)>(s[2 * I], s[2 * I + 1], c3c);
        ExpLoop<I + 1>::run(s, p, c3c);
    }
};
template <> struct ExpLoop<16> { static __device__ __forceinline__ void run(float (&)[32], uint32_t (&)[16], uint32_t) {} };
template <int I> struct InitLoop {
    static __device__ __forceinline__ void run(float (&s)[32]) {
        constexpr float v = init_of(I);
        s[2 * I] = v; s[2 * I + 1] = v;
        InitLoop<I + 1>::run(s);
    }
};
template <> struct InitLoop<16> { static __device__ __forceinline__ void run(float (&)[32]) {} };

__device__ __forceinline__ void flush_o(uint32_t (&o2)[6], const uint32_t (&o)[6]) {
#pragma unroll
    for (int i = 0; i < 6; i++) asm("{.reg .b32 c; mov.b32 c, 0x34003400; fma.rn.f16x2 %0, %1, c, %2;}" : "=r"(o2[i]) : "r"(o[i]), "r"(o2[i]));
}
__device__ __forceinline__ bool wg_any(int id, bool v) {
    uint32_t r;
    asm volatile("{\n.reg .pred p, q;\nsetp.ne.u32 q, %2, 0;\nbar.red.or.pred p, %1, 128, q;\nselp.u32 %0, 1, 0, p;\n}" : "=r"(r) : "r"(id), "r"((uint32_t)v) : "memory");
    return r;
}

__device__ __noinline__ void attn_slow(uint8_t* scr, const __nv_bfloat16* x, const __nv_bfloat16* w, int head, int rowtile, uint8_t* dst, int bar) {
    const int r = threadIdx.x & 63, hf = (threadIdx.x >> 6) & 1;
    float q[16], o[16], m = -INFINITY, l = 0.f;
#pragma unroll
    for (int d = 0; d < 16; d++) o[d] = 0.f;
    for (int c = -1; c < 32; c++) {
        const __nv_bfloat16* xr = x + ((c < 0 ? rowtile : c) * 64 + r) * D_;
        const __nv_bfloat16* wc = w + (c < 0 ? 0 : 512 + hf * 512) + head * 16;
        float a[16];
#pragma unroll
        for (int d = 0; d < 16; d++) a[d] = 0.f;
        for (int k2 = 0; k2 < 256; k2++) {
            const uint32_t xv = *(const uint32_t*)(xr + k2 * 2);
#pragma unroll
            for (int kk = 0; kk < 2; kk++) {
                const float xf = kk ? bhi(xv) : blo(xv);
                const uint4 w0 = *(const uint4*)(wc + (k2 * 2 + kk) * 1536), w1 = *(const uint4*)(wc + (k2 * 2 + kk) * 1536 + 8);
                const uint32_t ws[8] = {w0.x, w0.y, w0.z, w0.w, w1.x, w1.y, w1.z, w1.w};
#pragma unroll
                for (int d = 0; d < 8; d++) { a[2 * d] += xf * blo(ws[d]); a[2 * d + 1] += xf * bhi(ws[d]); }
            }
        }
        if (c < 0) {
#pragma unroll
            for (int d = 0; d < 16; d++) q[d] = rbf(a[d]);
            continue;
        }
        named_sync(bar, 128);
#pragma unroll
        for (int d = 0; d < 8; d++) ((uint32_t*)(scr + r * 64 + hf * 32))[d] = pack_b2(a[2 * d], a[2 * d + 1]);
        named_sync(bar, 128);
        for (int k = hf * 32; k < hf * 32 + 32; k++) {
            const uint32_t* kv = (const uint32_t*)(scr + k * 64);
            float s = 0.f;
#pragma unroll
            for (int d = 0; d < 8; d++) { s += q[2 * d] * blo(kv[d]); s += q[2 * d + 1] * bhi(kv[d]); }
            s = rbf(rbf(s) * 0.25f);
            const float mn = fmaxf(m, s), cr = __expf(m - mn), p = __expf(s - mn);
            l = l * cr + p;
            m = mn;
#pragma unroll
            for (int d = 0; d < 8; d++) { o[2 * d] = o[2 * d] * cr + p * blo(kv[8 + d]); o[2 * d + 1] = o[2 * d + 1] * cr + p * bhi(kv[8 + d]); }
        }
    }
    float* f = (float*)scr;
    named_sync(bar, 128);
    f[(hf * 64 + r) * 2] = m; f[(hf * 64 + r) * 2 + 1] = l;
    named_sync(bar, 128);
    const float m2 = f[((hf ^ 1) * 64 + r) * 2], l2 = f[((hf ^ 1) * 64 + r) * 2 + 1], mn = fmaxf(m, m2), cr = __expf(m - mn);
    const float sc = cr * frcp(l * cr + l2 * __expf(m2 - mn));
    named_sync(bar, 128);
#pragma unroll
    for (int d = 0; d < 8; d++) f[(d * 2 + hf) * 64 + r] = (hf ? o[d] : o[8 + d]) * sc;
    named_sync(bar, 128);
    float e[8];
#pragma unroll
    for (int d = 0; d < 8; d++) e[d] = (hf ? o[8 + d] : o[d]) * sc + f[(d * 2 + (hf ^ 1)) * 64 + r];
    *(uint4*)(dst + (r >> 3) * 256 + hf * 128 + (r & 7) * 16) = make_uint4(pack_b2(e[0], e[1]), pack_b2(e[2], e[3]), pack_b2(e[4], e[5]), pack_b2(e[6], e[7]));
    named_sync(bar, 128);
}

template <int V> struct IC { static constexpr int v = V; };
struct Params {
    const __nv_bfloat16 *x, *wqkv, *w_r, *gate_w, *wg, *wu, *wd;
};

__device__ __forceinline__ void mod_cta(uint8_t* smem, uint32_t sb, const Params& P, const CUtensorMap* mg, const CUtensorMap* mu,
                                        const CUtensorMap* md) {
    const int tid = threadIdx.x, lane = tid & 31, warp = tid >> 5, wg = tid >> 7, part = blockIdx.x - 128;
    const uint32_t bars = sb + OFF_MISC;
    constexpr int NBOX = 44;
    auto issue = [&](int i) {
        const int st = i % M_STAGES;
        const uint32_t bar = bars + 8 * (B_AF + st), dst = sb + st * M_STAGE_BYTES;
        if (i < 28) {
            const int j = i < 24 ? (i >> 3) * 2 + (i & 1) : 6, q = i < 24 ? (i >> 1) & 3 : i & 3;
            mbar_expect(bar, 32768);
            tma2d(dst, (q & 2) ? mu : mg, part * 448 + j * 64, (q & 1) * 256, bar);
        } else {
            mbar_expect(bar, 28672);
            tma2d(dst, md, (((i - 28) >> 2) * 2 + (i & 1)) * 64, part * 448 + ((i >> 1) & 1) * 224, bar);
        }
    };
    __syncthreads();
    if (tid == 512) {
        const uint32_t ep = g_epoch[blockIdx.x] + 1;
        for (int i = 0; i < M_STAGES; i++) issue(i);
        g_epoch[blockIdx.x] = ep;
        cnt_wait(C_R, 128 * ep);
    }
    for (int i = tid; i < 4096; i += NTHR) ((uint32_t*)(smem + OFF_XSEL))[i] = 0;
    __syncthreads();
    unsigned long long b1 = 0, b2 = 0;
    if (tid < 512) {
        const float4 rv = __ldcg((const float4*)(g_r + tid * 4));
        const float rr[4] = {rv.x, rv.y, rv.z, rv.w};
#pragma unroll
        for (int j = 0; j < 4; j++) {
            uint32_t u = __float_as_uint(rr[j]);
            u = (u & 0x80000000u) ? ~u : (u | 0x80000000u);
            const unsigned long long k = ((unsigned long long)u << 32) | (uint32_t)(~(tid * 4 + j));
            if (k > b1) { b2 = b1; b1 = k; } else if (k > b2) b2 = k;
        }
    }
    auto merge = [&](int o) {
        const unsigned long long c1 = __shfl_xor_sync(~0u, b1, o), c2 = __shfl_xor_sync(~0u, b2, o);
        const unsigned long long hi = b1 > c1 ? b1 : c1, lo = b1 > c1 ? c1 : b1, s2 = b2 > c2 ? b2 : c2;
        b1 = hi; b2 = lo > s2 ? lo : s2;
    };
    for (int o = 16; o; o >>= 1) merge(o);
    unsigned long long* red = (unsigned long long*)(smem + OFF_MISC + 512);
    if (lane == 0) { red[warp * 2] = b1; red[warp * 2 + 1] = b2; }
    __syncthreads();
    b1 = red[(lane & 15) * 2]; b2 = red[(lane & 15) * 2 + 1];
    for (int o = 8; o; o >>= 1) merge(o);
    const int i0 = (int)(~(uint32_t)b1), i1 = (int)(~(uint32_t)b2);
    if (tid < 128) {
        const int t = tid >> 6, kc = tid & 63;
        *(uint4*)(smem + OFF_XSEL + kc * 128 + t * 16) = *(const uint4*)(P.x + (t ? i1 : i0) * D_ + kc * 8);
    }
    if (part == 0 && tid == 0) {
        g_sel[0] = i0; g_sel[1] = i1;
        g_sel[2] = __float_as_int(rbf(sigmoidf_(__ldcg(g_r + i0))));
        g_sel[3] = __float_as_int(rbf(sigmoidf_(__ldcg(g_r + i1))));
    }
    fence_async_s();
    __syncthreads();
    if (tid == 512) {
        for (int i = M_STAGES; i < NBOX; i++) {
            mbar_wait(bars + 8 * (B_AE + i % M_STAGES), (i / M_STAGES - 1) & 1);
            issue(i);
        }
    } else if (wg < 2) {
        const int w4 = warp & 3, g = lane >> 2;
        auto box = [&](float (&acc)[4], int i, int nk, uint32_t boff, int first) {
            const int st = i % M_STAGES;
            mbar_wait(bars + 8 * (B_AF + st), (i / M_STAGES) & 1);
            const uint64_t da = mkdesc(0, 8192, 1024, 1) + st * (M_STAGE_BYTES >> 4), db = mkdesc(0, 128, 256, 0) + (boff >> 4);
            reg_fence(acc);
            wg_fence();
            for (int k = 0; k < nk; k++) wg_ss_n8_at(acc, da + k * 128, db + k * 16, !(first && k == 0));
            wg_commit();
            wg_wait<0>();
            reg_fence(acc);
            named_sync(3 + wg, 128);
            if ((tid & 127) == 0) mbar_arrive(bars + 8 * (B_AE + st));
        };
#pragma unroll 1
        for (int j = wg; j < 7; j += 2) {
            float ag[4] = {0, 0, 0, 0}, au[4] = {0, 0, 0, 0};
            const int i = (j >> 1) * 8 + wg, di = j < 6 ? 2 : 1;
            box(ag, i, 16, OFF_XSEL, 1); box(ag, i + di, 16, OFF_XSEL + 4096, 0);
            box(au, i + 2 * di, 16, OFF_XSEL, 1); box(au, i + 3 * di, 16, OFF_XSEL + 4096, 0);
            if ((lane & 3) == 0) {
#pragma unroll
                for (int e = 0; e < 4; e++) {
                    const float gv = rbf(ag[e]), h = rbf(gv * sigmoidf_(gv)) * rbf(au[e]);
                    const int f = j * 64 + w4 * 16 + (e >> 1) * 8 + g;
                    *(__nv_bfloat16*)(smem + OFF_HSEL + (f >> 3) * 128 + (e & 1) * 16 + (f & 7) * 2) = __float2bfloat16_rn(h);
                }
            }
        }
        fence_async_s();
        named_sync(1, 256);
#pragma unroll 1
        for (int j = wg; j < 8; j += 2) {
            float a[4] = {0, 0, 0, 0};
            const int i = 28 + (j >> 1) * 4 + wg;
            box(a, i, 14, OFF_HSEL, 1); box(a, i + 2, 14, OFF_HSEL + 14 * 256, 0);
            if ((lane & 3) == 0) {
#pragma unroll
                for (int e = 0; e < 4; e++) g_y[(part * 2 + (e & 1)) * D_ + j * 64 + w4 * 16 + (e >> 1) * 8 + g] = a[e];
            }
        }
        named_sync(1, 256);
        if (tid == 0) { cnt_arrive(C_Y); TSTAMP(1); }
    }
}

__global__ void __launch_bounds__(NTHR, 1)
fused_kernel(const __grid_constant__ CUtensorMap mx, const __grid_constant__ CUtensorMap mkv, const __grid_constant__ CUtensorMap mq,
             const __grid_constant__ CUtensorMap mo, const __grid_constant__ CUtensorMap mout, const __grid_constant__ CUtensorMap mg,
             const __grid_constant__ CUtensorMap mu, const __grid_constant__ CUtensorMap md, const __grid_constant__ Params P) {
    extern __shared__ __align__(1024) uint8_t smem[];
    constexpr uint32_t sb = SBASE, bars = sb + OFF_MISC;
    const int tid = threadIdx.x, lane = tid & 31, warp = __shfl_sync(~0u, tid >> 5, 0), wg = warp >> 2, w4 = warp & 3;
    const int cta = blockIdx.x;
    volatile uint32_t* misc = (volatile uint32_t*)(smem + OFF_MISC + 320);
    const int nt = cta >> 4, mt = cta & 15;
    const int rt = 2 * mt + (nt & 1), ct = nt >> 1;

    if (lane == 0) {
        if (warp == 16) {
            TSTAMP(0);
#pragma unroll
            for (int i = 0; i < 8; i++) mbar_init(bars + 8 * (B_AF + i), 1);
            fence_async_s();
            if (cta < 128) {
#pragma unroll
                for (int kc = 0; kc < 8; kc++) {
                    const uint32_t bar = bars + 8 * (B_AF + kc);
                    mbar_expect(bar, 32768);
                    tma2d(sb + off_x(kc), &mx, kc * 64, mt * 128, bar);
                    if (kc < 6) tma3d(sb + off_w(kc), &mkv, nt * 64, kc * 64, 1, bar);
                }
                TSTAMP(15);
            }
        } else if (wg < 4) {
            const uint32_t c = cta < 128 ? (uint32_t)(BAR_CNT >> (warp * 4)) & 15 : 0;
            mbar_init(bars + 8 * (8 + 2 * warp), c + 1);
            mbar_init(bars + 8 * (9 + 2 * warp), c + 1);
            fence_async_s();
            if ((uint32_t)__cvta_generic_to_shared(smem) != SBASE) __trap();
        }
    }
    __syncwarp();
    if (cta >= 128) {
        mod_cta(smem, sb, P, &mg, &mu, &md);
        return;
    }

    if (wg == 4) {
        asm volatile("setmaxnreg.dec.sync.aligned.u32 24;");
        uint32_t ep = g_epoch[cta] + 1;
        named_sync(7, NTHR);
        if (warp > 16) return;
        auto kv_stage = [&](int s) {
            const uint32_t bar = bars + 8 * (B_KF + (s & 3)), dst = sb + (s & 3) * SLOT;
            const uint8_t* src = g_kv + (nt * 16 + s) * 32768;
            mbar_expect(bar, 32768);
            bulk_ld(dst, src, 16384, bar);
            bulk_ld(dst + 18432, src + 16384, 16384, bar);
        };
        if (lane == 0) {
            misc[0] = ep;
            g_epoch[cta] = ep;
#pragma unroll 1
            for (int i = 0; i < 6; i++) {
                mbar_wait(bars + 8 * (B_AE + i), 0);
                if (i < 2) tma3d(sb + off_w(i), &mkv, nt * 64, (6 + i) * 64, 1, bars + 8 * (B_AF + 6 + i));
                else {
                    mbar_expect(bars + 8 * (B_QF + i - 2), 16384);
                    tma2d(sb + off_w(i), &mq, nt * 64, (i - 2) * 128, bars + 8 * (B_QF + i - 2));
                }
            }
            mbar_wait(bars + 8 * B_KVP, 0);
            TSTAMP(12);
            cnt_arrive(C_KV + nt);
            TSTAMP(3);
            cnt_wait(C_KV + nt, 16 * ep);
            TSTAMP(4);
            fence_async_g();
            kv_stage(0);
            mbar_wait(bars + 8 * B_AFREE, 0);
            for (int s = 1; s < 4; s++) kv_stage(s);
            mbar_expect(bars + 8 * B_WOE, 65536);
            for (int j = 0; j < 2; j++) tma4d(sb + OFF_WOE + j * 32768, &mo, ct * 128 + j * 64, 0, 0, 0, bars + 8 * B_WOE);
            l2_prefetch(P.wg + cta * 7168, 14336); l2_prefetch(P.wu + cta * 7168, 14336); l2_prefetch(P.wd + cta * 7168, 14336);
            mbar_wait(bars + 8 * B_MX, 0);
            cnt_arrive(C_MX + nt);
            cnt_wait(C_MX + nt, 16 * ep);
        }
        __syncwarp();
        {
            const uint4 v = __ldcg((const uint4*)(g_mx + nt * 128) + lane);
            uint32_t m = max(max(v.x, v.y), max(v.z, v.w));
            m = max(m, __shfl_xor_sync(~0u, m, 1));
            m = max(m, __shfl_xor_sync(~0u, m, 2));
            uint32_t qn = misc[8 + lane];
            qn = max(qn, __shfl_xor_sync(~0u, qn, 4));
            qn = max(qn, __shfl_xor_sync(~0u, qn, 8));
            qn = max(qn, __shfl_xor_sync(~0u, qn, 16));
            const float k2 = __uint_as_float(__shfl_sync(~0u, m, (lane & 3) * 4)), vm = __uint_as_float(__shfl_sync(~0u, m, 16 + (lane & 3) * 4));
            const float q2 = __uint_as_float(qn);
            if (lane < 4) misc[4 + lane] = q2 * k2 <= BOUND_MAX * BOUND_MAX && q2 <= 65536.f && k2 <= 65536.f && vm >= 0.03125f;
        }
        __syncwarp();
        if (lane == 0) {
#pragma unroll 1
            for (int s = 4; s < 16; s++) {
                mbar_wait(bars + 8 * (B_KF + ((s - 2) & 3)), ((s - 2) >> 2) & 1);
                kv_stage(s);
            }
            mbar_wait(bars + 8 * B_OP, 0);
            cnt_arrive(C_O + mt * 2);
            mbar_wait(bars + 8 * (B_KF + 2), 1);
            cnt_wait(C_O + mt * 2, 8 * ep);
            fence_async_g();
            mbar_expect(bars + 8 * B_KF, 32768);
            bulk_ld(sb, g_o + rt * 65536, 32768, bars + 8 * B_KF);
            for (int j = 0; j < 2; j++) {
                mbar_wait(bars + 8 * (B_KF + 3 - 3 * j), 1 - j);
                mbar_expect(bars + 8 * (B_WL + j), 32768);
                tma4d(sb + (1 + j) * SLOT, &mo, ct * 128 + j * 64, 0, 1, 0, bars + 8 * (B_WL + j));
            }
            mbar_wait(bars + 8 * (B_OP + 1), 0);
            TSTAMP(13);
            cnt_arrive(C_O + mt * 2 + 1);
            TSTAMP(7);
            cnt_wait(C_O + mt * 2 + 1, 8 * ep);
            TSTAMP(8);
            fence_async_g();
            for (int c = 0; c < 4; c++) {
                mbar_expect(bars + 8 * (B_OL + c), 8192);
                bulk_ld(sb + 3 * SLOT + c * 8192, g_o + rt * 65536 + 32768 + c * 8192, 8192, bars + 8 * (B_OL + c));
            }
        }
        return;
    }

    uint4 qa, qb;
    if (wg < 2) {
        if (wg == 0) {
            *(uint4*)(smem + 16384 + tid * 16) = make_uint4(0x3c003c00u, 0x3c003c00u, 0x3c003c00u, 0x3c003c00u);
            fence_async_s();
        }
        named_sync(7, NTHR);
        asm volatile("setmaxnreg.inc.sync.aligned.u32 112;");
        float acc[64];
#pragma unroll
        for (int kc = 0; kc < 8; kc++) {
            mbar_wait_u(bars + 8 * (B_AF + kc), 0);
            if (kc == 0 && tid == 0) TSTAMP(1);
            const uint64_t da = mkdesc(off_w(kc % 6), 8192, 1024, 1) + wg * 512, db = mkdesc(off_x(kc), 16, 1024, 1);
            wg_fence();
#pragma unroll
            for (int kk = 0; kk < 4; kk++) wg_ss_n128_at(acc, da + kk * 128, db + kk * 2, kc + kk > 0);
            wg_commit();
            if (kc >= 1 && kc <= 6) {
                wg_wait<1>();
                if ((tid & 127) == 0) mbar_arrive(bars + 8 * (B_AE + kc - 1));
            }
        }
        wg_wait<0>();
        reg_fence(acc);
        if (tid == 0) TSTAMP(2);
        const int st = w4 & 1, cg = mt & 7;
        uint8_t* img = g_kv + ((nt * 2 + (w4 >> 1)) * 8 + (mt >> 3) * 4) * 32768 + st * 16384 + lane * 4;
        uint32_t mxv;
        if (wg == 0) {
            uint8_t* dst = img + st * 6144 + cg * 256;
#pragma unroll
            for (int j = 0; j < 16; j++)
#pragma unroll
                for (int h = 0; h < 2; h++) {
                    const int i = 4 * j + 2 * h;
                    *(uint32_t*)(dst + (j >> 2) * 32768 + ((j >> 1) & 1) * 6144 + (j & 1) * 2048 + h * 128) =
                        j ? pack_h2(acc[i] - acc[i - 4], acc[i + 1] - acc[i - 3]) : pack_h2(acc[i], acc[i + 1]);
                }
            asm volatile("bar.arrive 8, 512;" ::: "memory");
            __syncwarp();
            if (lane == 0) mbar_arrive(bars + 8 * B_KVP);
            uint32_t n[16];
#pragma unroll
            for (int j = 0; j < 16; j++) n[j] = pack_b2(acc[4 * j] * acc[4 * j] + acc[4 * j + 2] * acc[4 * j + 2], acc[4 * j + 1] * acc[4 * j + 1] + acc[4 * j + 3] * acc[4 * j + 3]);
            auto fold = [&](auto oc) {
                constexpr int o = decltype(oc)::v;
                const bool up = lane & (2 * o);
#pragma unroll
                for (int i = 0; i < o; i++) {
                    const uint32_t t = __shfl_xor_sync(~0u, up ? n[i] : n[i + o], 2 * o), k = up ? n[i + o] : n[i];
                    asm("add.bf16x2 %0, %1, %2;" : "=r"(n[i]) : "r"(t), "r"(k));
                }
            };
            fold(IC<8>()); fold(IC<4>()); fold(IC<2>());
            mxv = max(max(n[0] << 16, n[0] & 0xffff0000u), max(n[1] << 16, n[1] & 0xffff0000u));
        } else {
            uint8_t* dst = img + cg * 128;
            const int o00 = st ? 0 : 12288;
            float mm = 0.f;
#pragma unroll
            for (int j = 0; j < 16; j++)
#pragma unroll
                for (int h = 0; h < 2; h++) {
                    const int i = 4 * j + 2 * h;
                    *(uint32_t*)(dst + (j >> 2) * 32768 + ((j & 2) ? 4096 + h * 6144 : o00 + h * 2048) + (j & 1) * 1024) = pack_h2(acc[i], acc[i + 1]);
                }
            asm volatile("bar.arrive 8, 512;" ::: "memory");
            __syncwarp();
            if (lane == 0) mbar_arrive(bars + 8 * B_KVP);
#pragma unroll
            for (int i = 0; i < 64; i++) mm = fmaxf(mm, fabsf(acc[i]));
            mxv = __float_as_uint(mm);
        }
        mxv = __reduce_max_sync(~0u, mxv);
        if (lane == 0) { g_mx[nt * 128 + warp * 16 + mt] = __uint_as_float(mxv); mbar_arrive(bars + 8 * B_MX); }
        named_sync(1, 512);
        const uint4* qx = (const uint4*)(smem + off_x(0) + wg * 8192) + (tid & 127);
        qa = qx[0]; qb = qx[128];
    } else {
        {
            const int row0 = cta * 16 + (warp - 8) * 2;
            uint4 xv[2][2], wr[2], wgt[2];
#pragma unroll
            for (int c = 0; c < 2; c++) {
#pragma unroll
                for (int r = 0; r < 2; r++) xv[r][c] = *(const uint4*)(P.x + (row0 + r) * D_ + c * 256 + lane * 8);
                wr[c] = *(const uint4*)(P.w_r + c * 256 + lane * 8);
                wgt[c] = *(const uint4*)(P.gate_w + c * 256 + lane * 8);
            }
            named_sync(7, NTHR);
            asm volatile("setmaxnreg.inc.sync.aligned.u32 112;");
            auto dot8 = [](uint4 a, uint4 b) {
                return blo(a.x) * blo(b.x) + bhi(a.x) * bhi(b.x) + blo(a.y) * blo(b.y) + bhi(a.y) * bhi(b.y) +
                       blo(a.z) * blo(b.z) + bhi(a.z) * bhi(b.z) + blo(a.w) * blo(b.w) + bhi(a.w) * bhi(b.w);
            };
#pragma unroll
            for (int r = 0; r < 2; r++) {
                float a = dot8(xv[r][0], wr[0]) + dot8(xv[r][1], wr[1]), b = dot8(xv[r][0], wgt[0]) + dot8(xv[r][1], wgt[1]);
#pragma unroll
                for (int o = 16; o; o >>= 1) { a += __shfl_xor_sync(~0u, a, o); b += __shfl_xor_sync(~0u, b, o); }
                if (lane == 0) { g_r[row0 + r] = rbf(a); g_g[row0 + r] = sigmoidf_(b); }
            }
            named_sync(2, 256);
            if (tid == 256) cnt_arrive(C_R);
            __syncwarp();
        }
        float acc[32];
        named_sync(8, 512);
#pragma unroll
        for (int kc = 0; kc < 8; kc++) {
            if (!(kc & 1)) mbar_wait_u(bars + 8 * (B_QF + (kc >> 1)), 0);
            mbar_wait_u(bars + 8 * (B_AF + kc), 0);
            const uint64_t da = mkdesc(off_x(kc), 16, 1024, 1) + (wg - 2) * 512, db = mkdesc(off_w(2 + (kc >> 1)) + (kc & 1) * 8192, 8192, 1024, 1);
            wg_fence();
#pragma unroll
            for (int kk = 0; kk < 4; kk++) wg_ss_n64_bt(acc, da + kk * 2, db + kk * 128, kc + kk > 0);
            wg_commit();
        }
        wg_wait<0>();
        reg_fence(acc);
        if (tid == 256) TSTAMP(14);
#pragma unroll
        for (int i = 0; i < 32; i++) acc[i] *= QSCALE;
        auto frag = [&](int h) {
            return make_uint4(pack_h2(acc[8 * h], acc[8 * h + 1]), pack_h2(acc[8 * h + 2], acc[8 * h + 3]),
                              pack_h2(acc[8 * h + 4], acc[8 * h + 5]), pack_h2(acc[8 * h + 6], acc[8 * h + 7]));
        };
        named_sync(3 + wg, 128);
        uint4* qx = (uint4*)(smem + off_x(0) + (wg - 2) * 8192) + (tid & 127);
        qx[0] = frag(0); qx[128] = frag(2);
        qa = frag(1); qb = frag(3);
        named_sync(1, 512);
#pragma unroll
        for (int i = 1; i < 4; i++) *(uint2*)(smem + i * SLOT + 16384 + (tid - 256) * 8) = make_uint2(0x3c003c00u, 0x3c003c00u);
        float nrm[8];
#pragma unroll
        for (int h = 0; h < 4; h++) {
            const float* k = &acc[8 * h];
            nrm[2 * h] = k[0] * k[0] + k[1] * k[1] + k[4] * k[4] + k[5] * k[5];
            nrm[2 * h + 1] = k[2] * k[2] + k[3] * k[3] + k[6] * k[6] + k[7] * k[7];
        }
        const bool o2 = lane & 2, o1 = lane & 1;
        float u[4];
#pragma unroll
        for (int i = 0; i < 4; i++) u[i] = (o2 ? nrm[4 + i] : nrm[i]) + __shfl_xor_sync(~0u, o2 ? nrm[i] : nrm[4 + i], 2);
        const float a = (o1 ? u[2] : u[0]) + __shfl_xor_sync(~0u, o1 ? u[0] : u[2], 1);
        const float b = (o1 ? u[3] : u[1]) + __shfl_xor_sync(~0u, o1 ? u[1] : u[3], 1);
        uint32_t m = max(__float_as_uint(a), __float_as_uint(b));
        m = max(m, __shfl_xor_sync(~0u, m, 4));
        m = max(m, __shfl_xor_sync(~0u, m, 8));
        m = max(m, __shfl_xor_sync(~0u, m, 16));
        if (lane < 4) misc[8 + (warp - 8) * 4 + lane] = m;
        fence_async_s();
        __syncwarp();
        if (lane == 0) mbar_arrive(bars + 8 * B_AFREE);
    }

    const int st = wg >> 1;
    uint8_t* const odst = g_o + (2 * mt + (wg & 1)) * 65536 + (nt * 2 + st) * 2048;
    uint32_t fail = 0;
    {
        float s[32];
        uint32_t o[6], o2[6];
        uint32_t q0 = qa.x, q1 = qa.y, q2 = qa.z, q3 = qa.w;
        uint32_t c3c = 0x3c003c00u;
        asm volatile("" : "+r"(c3c));
        const uint64_t dk0 = mkdesc(0, 128, 256, 0) + st * (24576 >> 4);
        const uint64_t dv0 = mkdesc(12288, 128, 2048, 0) + st * (4096 >> 4), dw0 = mkdesc(4096, 128, 6144, 0) + st * (12288 >> 4);
        const bool sig = (tid & 127) == 0;
        InitLoop<0>::run(s);
#pragma unroll
        for (int i = 0; i < 6; i++) o[i] = o2[i] = 0;
        reg_fence(s);
        reg_fence(o);
        if (sig) mbar_arrive(bars + 8 * B_KF);
        mbar_wait_u(bars + 8 * B_KF, 0);
        if (tid == 0) { TSTAMP(5); CSTAMP(30); }
        wg_fence();
        wg_rs_qk(s, q0, q1, q2, q3, dk0);
        wg_commit();
        wg_wait<0>();
        reg_fence(s);
#define ATT_BLOCK(U, PRE, DN, WAITN)                                                                              \
    {                                                                                                             \
        uint32_t p[16];                                                                                           \
        ExpLoop<0>::run(s, p, c3c);                                                                               \
        if (U == 3) { wg_wait<0>(); reg_fence(o); flush_o(o2, o); }                                               \
        PRE;                                                                                                      \
        wg_fence();                                                                                               \
        wg_rs_qk(s, q0, q1, q2, q3, DN);                                                                          \
        const uint64_t dp = (U < 2 ? dv : dw) + (U & 1) * 64;                                                     \
        if (U == 3) wg_rs_pv0(o, p[0], p[1], p[2], p[3], dp); else wg_rs_pv(o, p[0], p[1], p[2], p[3], dp);       \
        wg_rs_pv(o, p[4], p[5], p[6], p[7], dp + 16);                                                             \
        wg_commit();                                                                                              \
        wg_rs_pv(o, p[8], p[9], p[10], p[11], dp + 32);                                                           \
        wg_rs_pv(o, p[12], p[13], p[14], p[15], dp + 48);                                                         \
        wg_commit();                                                                                              \
        wg_wait<WAITN>();                                                                                         \
        if (U == ARR && sig) mbar_arrive(nb);                                                                     \
        reg_fence(s);                                                                                             \
    }
#define ATT_STAGE(I, PRE, DN, WAITN)                                                                              \
    {                                                                                                             \
        const uint64_t dk = dk0 + I * (SLOT >> 4), dv = dv0 + I * (SLOT >> 4), dw = dw0 + I * (SLOT >> 4);        \
        constexpr uint32_t nb = bars + 8 * (B_KF + ((I + 1) & 3));                                                \
        ATT_BLOCK(0, , dk + 128, 1)                                                                               \
        ATT_BLOCK(1, , dk + 384, 1)                                                                               \
        ATT_BLOCK(2, , dk + 512, 1)                                                                               \
        ATT_BLOCK(3, PRE, DN, WAITN)                                                                              \
    }
#pragma unroll 1
        for (int seg = 0; seg < 4; seg++) {
            ATT_STAGE(0, mbar_wait_u(nb, seg & 1), dk + (SLOT >> 4), 1)
            ATT_STAGE(1, mbar_wait_u(nb, seg & 1), dk + (SLOT >> 4), 1)
            ATT_STAGE(2, mbar_wait_u(nb, seg & 1), dk + (SLOT >> 4), 1)
            ATT_STAGE(3, { InitLoop<0>::run(s); reg_fence(s);
                           if (seg & 1) { q0 = qb.x; q1 = qb.y; q2 = qb.z; q3 = qb.w; }
                           if (seg < 3) mbar_wait_u(nb, ~seg & 1); }, seg < 3 ? dk0 : dk, 0)
            reg_fence(o);
            if (seg & 1) {
                flush_o(o2, o);
                const int ps = seg >> 1;
                const float l0 = h2f((st ? o2[0] : o2[4])).x, l1 = h2f(st ? o2[1] : o2[5]).x;
                const float i0 = frcp(l0), i1 = frcp(l1);
                float chk = 0.f;
                uint32_t* dst = (uint32_t*)(odst + ps * 32768 + w4 * 512) + lane;
#pragma unroll
                for (int i = 0; i < 4; i++) {
                    const uint32_t h = st ? o2[2 + i] : o2[i];
                    const float2 v = h2f(h);
                    chk += fabsf(v.x) + fabsf(v.y);
                    const float sc = (i & 1) ? i1 : i0;
                    dst[(i >> 1) * 32 + (i & 1) * 64] = pack_b2(v.x * sc, v.y * sc);
                }
                const bool ok = chk + l0 + l1 < 1e6f && l0 >= 128.f && l1 >= 128.f && misc[4 + 2 * ps + st];
                if (__all_sync(~0u, ok)) { if (lane == 0) mbar_arrive(bars + 8 * (B_OP + ps)); }
                else fail |= 1 << ps;
#pragma unroll
                for (int i = 0; i < 6; i++) o[i] = o2[i] = 0;
                reg_fence(o);
            }
        }
        if (tid == 0) { TSTAMP(6); CSTAMP(31); }
    }
    if (wg_any(3 + wg, fail)) {
        for (int ps = 0; ps < 2; ps++)
            if (wg_any(3 + wg, (fail >> ps) & 1)) {
                attn_slow(smem + OFF_STG + wg * 4096, P.x, P.wqkv, nt * 4 + 2 * ps + st, 2 * mt + (wg & 1), odst + ps * 32768, 3 + wg);
                if (((fail >> ps) & 1) && lane == 0) mbar_arrive(bars + 8 * (B_OP + ps));
            }
    }

    if (wg < 2) {
        float acc[32];
        const int row = rt * 64 + w4 * 16 + (lane >> 2), col = ct * 128 + wg * 64 + (lane & 3) * 2;
        uint32_t xr[16];
#pragma unroll
        for (int j = 0; j < 8; j++) {
            xr[2 * j] = *(const uint32_t*)(P.x + row * D_ + col + j * 8);
            xr[2 * j + 1] = *(const uint32_t*)(P.x + (row + 8) * D_ + col + j * 8);
        }
        mbar_wait_u(bars + 8 * B_WOE, 0);
        mbar_wait_u(bars + 8 * B_KF, 0);
        wg_fence();
#pragma unroll
        for (int k = 0; k < 16; k++) wg_ss_n64_bt(acc, mkdesc(k * 2048, 128, 256, 0), mkdesc(OFF_WOE + k * 2048, 8192, 1024, 1) + wg * 2048, k > 0);
        wg_commit();
        if (lane == 0) { const uint32_t ep = misc[0]; cnt_wait(C_Y, 4 * ep); cnt_wait(C_R, 128 * ep); }
        __syncwarp();
        const float g0 = __ldcg(g_g + row), g1 = __ldcg(g_g + row + 8);
        const int4 sel = __ldcg((const int4*)g_sel);
#pragma unroll
        for (int h = 0; h < 2; h++) {
            const int r = row + 8 * h;
            if (r == sel.x || r == sel.y) {
                const int t = r == sel.x ? 0 : 1;
                const float rs = __int_as_float(t ? sel.w : sel.z);
#pragma unroll
                for (int j = 0; j < 8; j++) {
                    float y0 = 0.f, y1 = 0.f;
#pragma unroll
                    for (int pp = 0; pp < 4; pp++) {
                        float2 v;
                        asm volatile("ld.global.cg.v2.f32 {%0, %1}, [%2];" : "=f"(v.x), "=f"(v.y) : "l"(g_y + (pp * 2 + t) * D_ + col + j * 8) : "memory");
                        y0 += v.x; y1 += v.y;
                    }
                    xr[2 * j + h] = pack_b2(blo(xr[2 * j + h]) + rbf(rbf(y0) * rs), bhi(xr[2 * j + h]) + rbf(rbf(y1) * rs));
                }
            }
        }
        __syncwarp();
        mbar_wait_u(bars + 8 * (B_WL + wg), 0);
#pragma unroll
        for (int c = 0; c < 4; c++) {
            mbar_wait_u(bars + 8 * (B_OL + c), 0);
            if (c == 0 && tid == 0) TSTAMP(9);
            wg_fence();
#pragma unroll
            for (int k = 4 * c; k < 4 * c + 4; k++)
                wg_ss_n64_bt(acc, mkdesc(3 * SLOT + k * 2048, 128, 256, 0), mkdesc(SLOT + k * 2048, 8192, 1024, 1) + wg * (SLOT >> 4), 1);
            wg_commit();
        }
        wg_wait<0>();
        reg_fence(acc);
        if (tid == 0) TSTAMP(10);
        const uint32_t stg = sb + OFF_STG + warp * 2048, sa = stg + (lane & 15) * 128;
#pragma unroll
        for (int j = 0; j < 8; j += 2) {
            uint32_t v[4];
#pragma unroll
            for (int e = 0; e < 4; e++) {
                const float g = (e & 1) ? g1 : g0;
                const uint32_t xx = xr[2 * j + e];
                v[e] = pack_b2(g * acc[4 * j + 2 * e] + (1.f - g) * blo(xx), g * acc[4 * j + 2 * e + 1] + (1.f - g) * bhi(xx));
            }
            asm volatile("stmatrix.sync.aligned.m8n8.x4.shared.b16 [%0], {%1, %2, %3, %4};"
                         ::"r"(sa + (((j + (lane >> 4)) ^ (lane & 7)) << 4)), "r"(v[0]), "r"(v[1]), "r"(v[2]), "r"(v[3]) : "memory");
        }
        fence_async_s();
        __syncwarp();
        if (lane == 0) {
            asm volatile("cp.async.bulk.tensor.2d.global.shared::cta.bulk_group [%0, {%1, %2}], [%3];"
                         ::"l"(&mout), "r"(ct * 128 + wg * 64), "r"(rt * 64 + w4 * 16), "r"(stg) : "memory");
            asm volatile("cp.async.bulk.commit_group;" ::: "memory");
            asm volatile("cp.async.bulk.wait_group.read 0;" ::: "memory");
            if (tid == 0) TSTAMP(11);
        }
    }
}

typedef CUresult (*EncodeFn)(CUtensorMap*, CUtensorMapDataType, cuuint32_t, void*, const cuuint64_t*, const cuuint64_t*, const cuuint32_t*,
                             const cuuint32_t*, CUtensorMapInterleave, CUtensorMapSwizzle, CUtensorMapL2promotion, CUtensorMapFloatOOBfill);

void make_map(EncodeFn fn, CUtensorMap* m, const void* p, int rank, const cuuint64_t* dims, const cuuint64_t* strides, const cuuint32_t* box) {
    cuuint32_t es[4] = {1, 1, 1, 1};
    fn(m, CU_TENSOR_MAP_DATA_TYPE_BFLOAT16, rank, (void*)p, dims, strides, box, es, CU_TENSOR_MAP_INTERLEAVE_NONE, CU_TENSOR_MAP_SWIZZLE_128B,
       CU_TENSOR_MAP_L2_PROMOTION_L2_128B, CU_TENSOR_MAP_FLOAT_OOB_FILL_NONE);
}
void make_map2(EncodeFn fn, CUtensorMap* m, const void* p, int rows, int cols, int box_rows) {
    cuuint64_t dims[2] = {(cuuint64_t)cols, (cuuint64_t)rows}, strides[1] = {(cuuint64_t)cols * 2};
    cuuint32_t box[2] = {64, (cuuint32_t)box_rows};
    make_map(fn, m, p, 2, dims, strides, box);
}

}

extern "C" void kernel_launch(void* const* d_in, const int* in_sizes, int n_in, void* d_out, int out_size) {
    static EncodeFn fn = nullptr;
    if (!fn) {
        void* f = nullptr;
        cudaDriverEntryPointQueryResult qr;
        cudaGetDriverEntryPoint("cuTensorMapEncodeTiled", &f, cudaEnableDefault, &qr);
        fn = (EncodeFn)f;
        cudaFuncSetAttribute(fused_kernel, cudaFuncAttributeMaxDynamicSharedMemorySize, SMEM_BYTES);
    }
    CUtensorMap mx, mkv, mq, mo, mout, mg, mu, md;
    make_map2(fn, &mx, d_in[0], S_, D_, 128);
    {
        cuuint64_t dims[3] = {512, 512, 3}, strides[2] = {3072, 1024};
        cuuint32_t box[3] = {64, 64, 2};
        make_map(fn, &mkv, d_in[1], 3, dims, strides, box);
    }
    make_map2(fn, &mq, d_in[1], D_, 3 * D_, 128);
    {
        cuuint64_t dims[4] = {512, 32, 2, 8}, strides[3] = {1024, 32768, 65536};
        cuuint32_t box[4] = {64, 32, 1, 8};
        make_map(fn, &mo, d_in[2], 4, dims, strides, box);
    }
    make_map2(fn, &mout, d_out, S_, D_, 16);
    make_map2(fn, &mg, d_in[5], D_, F_, 256);
    make_map2(fn, &mu, d_in[6], D_, F_, 256);
    make_map2(fn, &md, d_in[7], F_, D_, 224);
    Params P;
    P.x = (const __nv_bfloat16*)d_in[0];
    P.wqkv = (const __nv_bfloat16*)d_in[1];
    P.w_r = (const __nv_bfloat16*)d_in[4];
    P.gate_w = (const __nv_bfloat16*)d_in[8];
    P.wg = (const __nv_bfloat16*)d_in[5];
    P.wu = (const __nv_bfloat16*)d_in[6];
    P.wd = (const __nv_bfloat16*)d_in[7];
    fused_kernel<<<NCTA, NTHR, SMEM_BYTES, cudaStreamPerThread>>>(mx, mkv, mq, mo, mout, mg, mu, md, P);
}
```

```cpp
#include <cuda_runtime.h>
#include <cuda_bf16.h>
#include <cuda_fp16.h>
#include <cuda.h>
#include <stdint.h>

namespace {

constexpr int S_ = 2048, D_ = 512, F_ = 1792;
constexpr int NCTA = 132, NTHR = 640;
constexpr uint32_t SBASE = 0x400;
constexpr int SMEM_BYTES = 232448;

__host__ __device__ constexpr int off_w(int i) { return i == 0 ? 0 : 2048 + i * 16384; }
__host__ __device__ constexpr int off_x(int c) { return 100352 + (7 - c) * 16384; }
constexpr int SLOT = 34816;
constexpr int OFF_WOE = 4 * SLOT;
constexpr int OFF_STG = OFF_WOE + 65536;
__host__ __device__ constexpr int off_ol(int c) { return (c < 2 ? 3 * SLOT : OFF_STG) + (c & 1) * 8192; }
constexpr int OFF_BSEL = OFF_STG + 24576;
constexpr int OFF_INIT = OFF_BSEL + 512;
constexpr int OFF_MISC = 231424;
constexpr int M_STAGES = 6, M_STAGE_BYTES = 32768;
constexpr int OFF_XSEL = M_STAGES * M_STAGE_BYTES, OFF_HSEL = OFF_XSEL + 8192;
constexpr int B_AF = 0, B_AE = 8, B_QF = 14, B_AFREE = 18, B_KVP = 19, B_KF = 20, B_WL = 24, B_OE = 25, B_WOE = 26, B_OP = 28, B_OL = 30, B_TRG = 35, B_GO = 36, B_HOLD = 38, B_CHK = 39;
constexpr unsigned long long BAR_CNT = 0x07733f0044700111ull;
constexpr int C_KV = 0, C_O = 8, C_R = 40, C_Y = 41, C_U = 42, NCNT = 50;

#define EXP_PAT 0x3333303033333030ull
constexpr unsigned long long PAT = EXP_PAT;
__host__ __device__ constexpr int pat_of(int i) { return (int)((PAT >> (4 * i)) & 15); }
constexpr float U0 = 14.f, OFF_C = 1.585497f, OFF_E = 2.083684f;
__host__ __device__ constexpr float init_of_t(int t) {
    return t == 0 ? U0 - 15.f + OFF_E : t == 2 ? 32.f + U0 + OFF_E - OFF_C : 32.f + U0;
}
#define TRGST 1
#define GOJ 7
#define QGO 15
#define HOLD 0
#define FL8 0
#define ARR 0
constexpr float BOUND_MAX = 17.2f;
constexpr float QSCALE = 0.25f * 1.4426950408889634f;

#define NTX ((cta & 3) | (cta >> 6 & 1) << 2)
#define MTX (cta >> 2 & 15)
__device__ __align__(1024) uint8_t g_kv[8 * 2 * 8 * 32768];
__device__ __align__(1024) uint8_t g_o[32 * 65536];
__device__ __align__(16) float g_mx[8 * 128];
__device__ __align__(16) float g_r[S_];
__device__ __align__(16) float g_g[S_];
__device__ __align__(16) float g_y[4 * 2 * D_];
__device__ __align__(16) int g_sel[4];
__device__ uint32_t g_cnt[NCNT * 32];
__device__ uint32_t g_epoch[NCTA];
#define TSTAMP(i)
#define CSTAMP(i)

__device__ __forceinline__ void wg_ss_n128_at(float (&d)[64], uint64_t da, uint64_t db, int acc) {
  asm volatile("{\n.reg .pred p;\nsetp.ne.b32 p, %66, 0;\n"
      "wgmma.mma_async.sync.aligned.m64n128k16.f32.bf16.bf16 {%0,%1,%2,%3,%4,%5,%6,%7,%8,%9,%10,%11,%12,%13,%14,%15,%16,%17,%18,%19,%20,%21,%22,%23,"
      "%24,%25,%26,%27,%28,%29,%30,%31,%32,%33,%34,%35,%36,%37,%38,%39,%40,%41,%42,%43,%44,%45,%46,%47,"
      "%48,%49,%50,%51,%52,%53,%54,%55,%56,%57,%58,%59,%60,%61,%62,%63}, %64, %65, p, 1, 1, 1, 0;\n}\n"
    : "+f"(d[0]), "+f"(d[1]), "+f"(d[2]), "+f"(d[3]), "+f"(d[4]), "+f"(d[5]), "+f"(d[6]), "+f"(d[7]), "+f"(d[8]), "+f"(d[9]), "+f"(d[10]), "+f"(d[11]),
      "+f"(d[12]), "+f"(d[13]), "+f"(d[14]), "+f"(d[15]), "+f"(d[16]), "+f"(d[17]), "+f"(d[18]), "+f"(d[19]), "+f"(d[20]), "+f"(d[21]), "+f"(d[22]), "+f"(d[23]),
      "+f"(d[24]), "+f"(d[25]), "+f"(d[26]), "+f"(d[27]), "+f"(d[28]), "+f"(d[29]), "+f"(d[30]), "+f"(d[31]), "+f"(d[32]), "+f"(d[33]), "+f"(d[34]), "+f"(d[35]),
      "+f"(d[36]), "+f"(d[37]), "+f"(d[38]), "+f"(d[39]), "+f"(d[40]), "+f"(d[41]), "+f"(d[42]), "+f"(d[43]), "+f"(d[44]), "+f"(d[45]), "+f"(d[46]), "+f"(d[47]),
      "+f"(d[48]), "+f"(d[49]), "+f"(d[50]), "+f"(d[51]), "+f"(d[52]), "+f"(d[53]), "+f"(d[54]), "+f"(d[55]), "+f"(d[56]), "+f"(d[57]), "+f"(d[58]), "+f"(d[59]),
      "+f"(d[60]), "+f"(d[61]), "+f"(d[62]), "+f"(d[63])
    : "l"(da), "l"(db), "r"(acc));
}
__device__ __forceinline__ void wg_ss_n128_bt(float (&d)[64], uint64_t da, uint64_t db, int acc) {
  asm volatile("{\n.reg .pred p;\nsetp.ne.b32 p, %66, 0;\n"
      "wgmma.mma_async.sync.aligned.m64n128k16.f32.bf16.bf16 {%0,%1,%2,%3,%4,%5,%6,%7,%8,%9,%10,%11,%12,%13,%14,%15,%16,%17,%18,%19,%20,%21,%22,%23,"
      "%24,%25,%26,%27,%28,%29,%30,%31,%32,%33,%34,%35,%36,%37,%38,%39,%40,%41,%42,%43,%44,%45,%46,%47,"
      "%48,%49,%50,%51,%52,%53,%54,%55,%56,%57,%58,%59,%60,%61,%62,%63}, %64, %65, p, 1, 1, 0, 1;\n}\n"
    : "+f"(d[0]), "+f"(d[1]), "+f"(d[2]), "+f"(d[3]), "+f"(d[4]), "+f"(d[5]), "+f"(d[6]), "+f"(d[7]), "+f"(d[8]), "+f"(d[9]), "+f"(d[10]), "+f"(d[11]),
      "+f"(d[12]), "+f"(d[13]), "+f"(d[14]), "+f"(d[15]), "+f"(d[16]), "+f"(d[17]), "+f"(d[18]), "+f"(d[19]), "+f"(d[20]), "+f"(d[21]), "+f"(d[22]), "+f"(d[23]),
      "+f"(d[24]), "+f"(d[25]), "+f"(d[26]), "+f"(d[27]), "+f"(d[28]), "+f"(d[29]), "+f"(d[30]), "+f"(d[31]), "+f"(d[32]), "+f"(d[33]), "+f"(d[34]), "+f"(d[35]),
      "+f"(d[36]), "+f"(d[37]), "+f"(d[38]), "+f"(d[39]), "+f"(d[40]), "+f"(d[41]), "+f"(d[42]), "+f"(d[43]), "+f"(d[44]), "+f"(d[45]), "+f"(d[46]), "+f"(d[47]),
      "+f"(d[48]), "+f"(d[49]), "+f"(d[50]), "+f"(d[51]), "+f"(d[52]), "+f"(d[53]), "+f"(d[54]), "+f"(d[55]), "+f"(d[56]), "+f"(d[57]), "+f"(d[58]), "+f"(d[59]),
      "+f"(d[60]), "+f"(d[61]), "+f"(d[62]), "+f"(d[63])
    : "l"(da), "l"(db), "r"(acc));
}
__device__ __forceinline__ void wg_ss_n64_bt(float (&d)[32], uint64_t da, uint64_t db, int acc) {
  asm volatile("{\n.reg .pred p;\nsetp.ne.b32 p, %34, 0;\n"
      "wgmma.mma_async.sync.aligned.m64n64k16.f32.bf16.bf16 {%0,%1,%2,%3,%4,%5,%6,%7,%8,%9,%10,%11,%12,%13,%14,%15,%16,%17,%18,%19,%20,%21,%22,%23,"
      "%24,%25,%26,%27,%28,%29,%30,%31}, %32, %33, p, 1, 1, 0, 1;\n}\n"
    : "+f"(d[0]), "+f"(d[1]), "+f"(d[2]), "+f"(d[3]), "+f"(d[4]), "+f"(d[5]), "+f"(d[6]), "+f"(d[7]), "+f"(d[8]), "+f"(d[9]), "+f"(d[10]), "+f"(d[11]),
      "+f"(d[12]), "+f"(d[13]), "+f"(d[14]), "+f"(d[15]), "+f"(d[16]), "+f"(d[17]), "+f"(d[18]), "+f"(d[19]), "+f"(d[20]), "+f"(d[21]), "+f"(d[22]), "+f"(d[23]),
      "+f"(d[24]), "+f"(d[25]), "+f"(d[26]), "+f"(d[27]), "+f"(d[28]), "+f"(d[29]), "+f"(d[30]), "+f"(d[31])
    : "l"(da), "l"(db), "r"(acc));
}
__device__ __forceinline__ void wg_ss_n8_at(float (&d)[4], uint64_t da, uint64_t db, int acc) {
  asm volatile("{\n.reg .pred p;\nsetp.ne.b32 p, %6, 0;\n"
      "wgmma.mma_async.sync.aligned.m64n8k16.f32.bf16.bf16 {%0,%1,%2,%3}, %4, %5, p, 1, 1, 1, 0;\n}\n"
    : "+f"(d[0]), "+f"(d[1]), "+f"(d[2]), "+f"(d[3])
    : "l"(da), "l"(db), "r"(acc));
}
__device__ __forceinline__ void wg_rs_qk(float (&d)[32], uint32_t a0, uint32_t a1, uint32_t a2, uint32_t a3, uint64_t db) {
  asm volatile("wgmma.mma_async.sync.aligned.m64n64k16.f32.f16.f16 {%0,%1,%2,%3,%4,%5,%6,%7,%8,%9,%10,%11,%12,%13,%14,%15,%16,%17,%18,%19,%20,%21,%22,%23,"
      "%24,%25,%26,%27,%28,%29,%30,%31}, {%32,%33,%34,%35}, %36, 1, 1, 1, 1;\n"
    : "+f"(d[0]), "+f"(d[1]), "+f"(d[2]), "+f"(d[3]), "+f"(d[4]), "+f"(d[5]), "+f"(d[6]), "+f"(d[7]), "+f"(d[8]), "+f"(d[9]), "+f"(d[10]), "+f"(d[11]),
      "+f"(d[12]), "+f"(d[13]), "+f"(d[14]), "+f"(d[15]), "+f"(d[16]), "+f"(d[17]), "+f"(d[18]), "+f"(d[19]), "+f"(d[20]), "+f"(d[21]), "+f"(d[22]), "+f"(d[23]),
      "+f"(d[24]), "+f"(d[25]), "+f"(d[26]), "+f"(d[27]), "+f"(d[28]), "+f"(d[29]), "+f"(d[30]), "+f"(d[31])
    : "r"(a0), "r"(a1), "r"(a2), "r"(a3), "l"(db));
}
__device__ __forceinline__ void wg_rs_pv(uint32_t (&d)[6], uint32_t a0, uint32_t a1, uint32_t a2, uint32_t a3, uint64_t db) {
  asm volatile("wgmma.mma_async.sync.aligned.m64n24k16.f16.f16.f16 {%0,%1,%2,%3,%4,%5}, {%6,%7,%8,%9}, %10, 1, 1, 1, 0;\n"
    : "+r"(d[0]), "+r"(d[1]), "+r"(d[2]), "+r"(d[3]), "+r"(d[4]), "+r"(d[5])
    : "r"(a0), "r"(a1), "r"(a2), "r"(a3), "l"(db));
}
__device__ __forceinline__ void wg_rs_pv0(uint32_t (&d)[6], uint32_t a0, uint32_t a1, uint32_t a2, uint32_t a3, uint64_t db) {
  asm volatile("wgmma.mma_async.sync.aligned.m64n24k16.f16.f16.f16 {%0,%1,%2,%3,%4,%5}, {%6,%7,%8,%9}, %10, 0, 1, 1, 0;\n"
    : "+r"(d[0]), "+r"(d[1]), "+r"(d[2]), "+r"(d[3]), "+r"(d[4]), "+r"(d[5])
    : "r"(a0), "r"(a1), "r"(a2), "r"(a3), "l"(db));
}

__device__ __forceinline__ void wg_fence() { asm volatile("wgmma.fence.sync.aligned;" ::: "memory"); }
__device__ __forceinline__ void wg_commit() { asm volatile("wgmma.commit_group.sync.aligned;" ::: "memory"); }
template <int N> __device__ __forceinline__ void wg_wait() { asm volatile("wgmma.wait_group.sync.aligned %0;" ::"n"(N) : "memory"); }
template <int N> __device__ __forceinline__ void reg_fence(float (&r)[N]) {
#pragma unroll
    for (int i = 0; i < N; i++) asm volatile("" : "+f"(r[i])::"memory");
}
template <int N> __device__ __forceinline__ void reg_fence(uint32_t (&r)[N]) {
#pragma unroll
    for (int i = 0; i < N; i++) asm volatile("" : "+r"(r[i])::"memory");
}
__device__ __forceinline__ void mbar_init(uint32_t bar, int cnt) { asm volatile("mbarrier.init.shared::cta.b64 [%0], %1;" ::"r"(bar), "r"(cnt) : "memory"); }
__device__ __forceinline__ void mbar_expect(uint32_t bar, int bytes) { asm volatile("mbarrier.arrive.expect_tx.shared::cta.b64 _, [%0], %1;" ::"r"(bar), "r"(bytes) : "memory"); }
__device__ __forceinline__ void mbar_arrive(uint32_t bar) { asm volatile("mbarrier.arrive.shared::cta.b64 _, [%0];" ::"r"(bar) : "memory"); }
__device__ __forceinline__ void mbar_wait(uint32_t bar, int parity) {
    asm volatile("{\n.reg .pred p;\n.reg .u32 n;\nmov.u32 n, 0;\n"
                 "W_%=:\nmbarrier.try_wait.parity.shared::cta.b64 p, [%0], %1;\n@p bra D_%=;\n"
                 "add.u32 n, n, 1;\nsetp.lt.u32 p, n, 0x4000000;\n@p bra W_%=;\ntrap;\nD_%=:\n}" ::"r"(bar), "r"(parity) : "memory");
}
__device__ __forceinline__ void mbar_wait_u(uint32_t bar, int parity) {
    for (uint32_t n = 0;; n++) {
        uint32_t ok;
        asm volatile("{\n.reg .pred p;\nmbarrier.try_wait.parity.shared::cta.b64 p, [%1], %2;\nselp.u32 %0, 1, 0, p;\n}" : "=r"(ok) : "r"(bar), "r"(parity) : "memory");
        if (__all_sync(~0u, ok)) break;
        if (n > 0x4000000u) __trap();
    }
}
__device__ __forceinline__ uint32_t mbar_probe(uint32_t bar, int parity) {
    uint32_t ok;
    asm volatile("{\n.reg .pred p;\nmbarrier.test_wait.parity.shared::cta.b64 p, [%1], %2;\nselp.u32 %0, 1, 0, p;\n}" : "=r"(ok) : "r"(bar), "r"(parity) : "memory");
    return ok;
}
__device__ __forceinline__ void mbar_finish(uint32_t ok, uint32_t bar, int parity) {
    asm volatile("{\n.reg .pred p;\n.reg .u32 n;\nsetp.ne.u32 p, %2, 0;\n@p bra.uni D_%=;\nmov.u32 n, 0;\n"
                 "W_%=:\nmbarrier.try_wait.parity.shared::cta.b64 p, [%0], %1;\n@p bra.uni D_%=;\n"
                 "add.u32 n, n, 1;\nsetp.lt.u32 p, n, 0x4000000;\n@p bra.uni W_%=;\ntrap;\nD_%=:\n}" ::"r"(bar), "r"(parity), "r"(ok) : "memory");
}
__device__ __forceinline__ void tma2d(uint32_t dst, const CUtensorMap* m, int c0, int c1, uint32_t bar) {
    asm volatile("cp.async.bulk.tensor.2d.shared::cluster.global.mbarrier::complete_tx::bytes [%0], [%1, {%2, %3}], [%4];"
                 ::"r"(dst), "l"(m), "r"(c0), "r"(c1), "r"(bar) : "memory");
}
__device__ __forceinline__ void tma3d(uint32_t dst, const CUtensorMap* m, int c0, int c1, int c2, uint32_t bar) {
    asm volatile("cp.async.bulk.tensor.3d.shared::cluster.global.mbarrier::complete_tx::bytes [%0], [%1, {%2, %3, %4}], [%5];"
                 ::"r"(dst), "l"(m), "r"(c0), "r"(c1), "r"(c2), "r"(bar) : "memory");
}
__device__ __forceinline__ void tma4d(uint32_t dst, const CUtensorMap* m, int c0, int c1, int c2, int c3, uint32_t bar) {
    asm volatile("cp.async.bulk.tensor.4d.shared::cluster.global.mbarrier::complete_tx::bytes [%0], [%1, {%2, %3, %4, %5}], [%6];"
                 ::"r"(dst), "l"(m), "r"(c0), "r"(c1), "r"(c2), "r"(c3), "r"(bar) : "memory");
}
__device__ __forceinline__ void l2_prefetch(const void* src, int bytes) {
    asm volatile("cp.async.bulk.prefetch.L2.global [%0], %1;" ::"l"(src), "r"(bytes) : "memory");
}
__device__ __forceinline__ void bulk_ld(uint32_t dst, const void* src, int bytes, uint32_t bar) {
    asm volatile("cp.async.bulk.shared::cluster.global.mbarrier::complete_tx::bytes [%0], [%1], %2, [%3];"
                 ::"r"(dst), "l"(src), "r"(bytes), "r"(bar) : "memory");
}
__device__ __forceinline__ void fence_async_s() { asm volatile("fence.proxy.async.shared::cta;" ::: "memory"); }
__device__ __forceinline__ void fence_async_g() { asm volatile("fence.proxy.async.global;" ::: "memory"); }
__device__ __forceinline__ void cnt_arrive(int i) {
    asm volatile("red.release.gpu.global.add.u32 [%0], 1;" ::"l"(&g_cnt[i * 32]) : "memory");
}
__device__ __forceinline__ void cnt_wait(int i, uint32_t target) {
    for (uint32_t n = 0;; n++) {
        uint32_t v;
        asm volatile("ld.acquire.gpu.global.u32 %0, [%1];" : "=r"(v) : "l"(&g_cnt[i * 32]) : "memory");
        if ((int)(v - target) >= 0) break;
        if (n > 0x800000u) __trap();
    }
}
__device__ __forceinline__ void named_sync(int id, int n) { asm volatile("bar.sync %0, %1;" ::"r"(id), "r"(n) : "memory"); }
__device__ __forceinline__ uint32_t pack_h2(float lo, float hi) { uint32_t r; asm("cvt.rn.f16x2.f32 %0, %1, %2;" : "=r"(r) : "f"(hi), "f"(lo)); return r; }
__device__ __forceinline__ uint32_t pack_b2(float lo, float hi) { uint32_t r; asm("cvt.rn.bf16x2.f32 %0, %1, %2;" : "=r"(r) : "f"(hi), "f"(lo)); return r; }
__device__ __forceinline__ float2 h2f(uint32_t v) {
    float2 r;
    asm("{.reg .b16 a, b; mov.b32 {a, b}, %2; cvt.f32.f16 %0, a; cvt.f32.f16 %1, b;}" : "=f"(r.x), "=f"(r.y) : "r"(v));
    return r;
}
__device__ __forceinline__ float blo(uint32_t v) { return __uint_as_float(v << 16); }
__device__ __forceinline__ float bhi(uint32_t v) { return __uint_as_float(v & 0xffff0000u); }
__device__ __forceinline__ float rbf(float v) { return __bfloat162float(__float2bfloat16_rn(v)); }
__device__ __forceinline__ float frcp(float v) { float r; asm("rcp.approx.ftz.f32 %0, %1;" : "=f"(r) : "f"(v)); return r; }
__device__ __forceinline__ float sigmoidf_(float v) { return frcp(1.f + __expf(-v)); }
__host__ __device__ constexpr uint64_t mkdesc(uint32_t off, uint32_t lbo, uint32_t sbo, uint32_t swz) {
    return (uint64_t)((SBASE + off) >> 4) | ((uint64_t)(lbo >> 4) << 16) | ((uint64_t)(sbo >> 4) << 32) | ((uint64_t)swz << 62);
}

template <int T> __device__ __forceinline__ uint32_t exp_pair(float a, float b, uint32_t c3c) {
    uint32_t r;
    if (T == 0) {
        float x, y;
        asm("ex2.approx.ftz.f32 %0, %1;" : "=f"(x) : "f"(a));
        asm("ex2.approx.ftz.f32 %0, %1;" : "=f"(y) : "f"(b));
        r = pack_h2(x, y);
    } else {
        uint32_t y;
        asm("prmt.b32 %0, %1, %2, 0x6521;" : "=r"(y) : "r"(__float_as_uint(a)), "r"(__float_as_uint(b)));
        if (T == 2) {
            uint32_t m, e = y | 0x03ff03ffu;
            asm("lop3.b32 %0, %1, 0x03ff03ff, %2, 0xea;" : "=r"(m) : "r"(y), "r"(c3c));
            asm("fma.rn.relu.f16x2 %0, %1, %2, %3;" : "=r"(r) : "r"(y), "r"(m), "r"(e));
        } else {
            uint32_t z = 0xfbdafbdau - y, w;
            asm("{.reg .b32 c; mov.b32 c, 0x45304530; fma.rn.f16x2 %0, %1, %2, c;}" : "=r"(w) : "r"(y), "r"(z));
            asm("fma.rn.relu.f16x2 %0, %1, %2, %1;" : "=r"(r) : "r"(y), "r"(w));
        }
    }
    return r;
}
template <int I> struct ExpLoop {
    static __device__ __forceinline__ void run(float (&s)[32], uint32_t (&p)[16], uint32_t c3c) {
        p[I] = exp_pair<pat_of(I)>(s[2 * I], s[2 * I + 1], c3c);
        ExpLoop<I + 1>::run(s, p, c3c);
    }
};
template <> struct ExpLoop<16> { static __device__ __forceinline__ void run(float (&)[32], uint32_t (&)[16], uint32_t) {} };
__device__ __forceinline__ void init_s(float (&s)[32]) {
#pragma unroll
    for (int j = 0; j < 8; j++)
        asm volatile("ld.shared.v4.f32 {%0, %1, %2, %3}, [%4];" : "=f"(s[4 * j]), "=f"(s[4 * j + 1]), "=f"(s[4 * j + 2]), "=f"(s[4 * j + 3])
                     : "r"(SBASE + OFF_INIT + 16 * j));
}
__device__ __forceinline__ uint32_t hfma2(uint32_t a, uint32_t b, uint32_t c) { uint32_t r; asm("fma.rn.f16x2 %0, %1, %2, %3;" : "=r"(r) : "r"(a), "r"(b), "r"(c)); return r; }
__device__ __forceinline__ bool wg_any(int id, bool v) {
    uint32_t r;
    asm volatile("{\n.reg .pred p, q;\nsetp.ne.u32 q, %2, 0;\nbar.red.or.pred p, %1, 128, q;\nselp.u32 %0, 1, 0, p;\n}" : "=r"(r) : "r"(id), "r"((uint32_t)v) : "memory");
    return r;
}

__device__ __noinline__ void attn_slow(uint8_t* scr, const __nv_bfloat16* x, const __nv_bfloat16* w, int head, int rowtile, uint8_t* dst, int frag, float gate, int bar) {
    const int r = threadIdx.x & 63, hf = (threadIdx.x >> 6) & 1;
    float q[16], o[16], m = -INFINITY, l = 0.f;
#pragma unroll
    for (int d = 0; d < 16; d++) o[d] = 0.f;
    for (int c = -1; c < 32; c++) {
        const __nv_bfloat16* xr = x + ((c < 0 ? rowtile : c) * 64 + r) * D_;
        const __nv_bfloat16* wc = w + (c < 0 ? 0 : 512 + hf * 512) + head * 16;
        float a[16];
#pragma unroll
        for (int d = 0; d < 16; d++) a[d] = 0.f;
        for (int k2 = 0; k2 < 256; k2++) {
            const uint32_t xv = *(const uint32_t*)(xr + k2 * 2);
#pragma unroll
            for (int kk = 0; kk < 2; kk++) {
                const float xf = kk ? bhi(xv) : blo(xv);
                const uint4 w0 = *(const uint4*)(wc + (k2 * 2 + kk) * 1536), w1 = *(const uint4*)(wc + (k2 * 2 + kk) * 1536 + 8);
                const uint32_t ws[8] = {w0.x, w0.y, w0.z, w0.w, w1.x, w1.y, w1.z, w1.w};
#pragma unroll
                for (int d = 0; d < 8; d++) { a[2 * d] += xf * blo(ws[d]); a[2 * d + 1] += xf * bhi(ws[d]); }
            }
        }
        if (c < 0) {
#pragma unroll
            for (int d = 0; d < 16; d++) q[d] = rbf(a[d]);
            continue;
        }
        named_sync(bar, 128);
#pragma unroll
        for (int d = 0; d < 8; d++) ((uint32_t*)(scr + r * 64 + hf * 32))[d] = pack_b2(a[2 * d], a[2 * d + 1]);
        named_sync(bar, 128);
        for (int k = hf * 32; k < hf * 32 + 32; k++) {
            const uint32_t* kv = (const uint32_t*)(scr + k * 64);
            float s = 0.f;
#pragma unroll
            for (int d = 0; d < 8; d++) { s += q[2 * d] * blo(kv[d]); s += q[2 * d + 1] * bhi(kv[d]); }
            s = rbf(rbf(s) * 0.25f);
            const float mn = fmaxf(m, s), cr = __expf(m - mn), p = __expf(s - mn);
            l = l * cr + p;
            m = mn;
#pragma unroll
            for (int d = 0; d < 8; d++) { o[2 * d] = o[2 * d] * cr + p * blo(kv[8 + d]); o[2 * d + 1] = o[2 * d + 1] * cr + p * bhi(kv[8 + d]); }
        }
    }
    float* f = (float*)scr;
    named_sync(bar, 128);
    f[(hf * 64 + r) * 2] = m; f[(hf * 64 + r) * 2 + 1] = l;
    named_sync(bar, 128);
    const float m2 = f[((hf ^ 1) * 64 + r) * 2], l2 = f[((hf ^ 1) * 64 + r) * 2 + 1], mn = fmaxf(m, m2), cr = __expf(m - mn);
    const float sc = gate * cr * frcp(l * cr + l2 * __expf(m2 - mn));
    named_sync(bar, 128);
#pragma unroll
    for (int d = 0; d < 8; d++) f[(d * 2 + hf) * 64 + r] = (hf ? o[d] : o[8 + d]) * sc;
    named_sync(bar, 128);
    float e[8];
#pragma unroll
    for (int d = 0; d < 8; d++) e[d] = (hf ? o[8 + d] : o[d]) * sc + f[(d * 2 + (hf ^ 1)) * 64 + r];
#pragma unroll
    for (int t = 0; t < 4; t++)
        *(uint32_t*)(dst + (frag ? (r >> 4) * 512 + (r & 7) * 64 + t * 16 + hf * 8 + ((r >> 3) & 1) * 4 : (r >> 3) * 256 + hf * 128 + (r & 7) * 16 + t * 4)) =
            pack_b2(e[2 * t], e[2 * t + 1]);
    named_sync(bar, 128);
}

template <int V> struct IC { static constexpr int v = V; };
struct Params {
    const __nv_bfloat16 *x, *wqkv, *w_r, *gate_w, *wg, *wu, *wd, *wo;
};

__device__ __forceinline__ void mod_cta(uint8_t* smem, uint32_t sb, const Params& P, const CUtensorMap* mg, const CUtensorMap* mu,
                                        const CUtensorMap* md) {
    const int tid = threadIdx.x, lane = tid & 31, warp = tid >> 5, wg = tid >> 7, part = blockIdx.x - 128;
    const uint32_t bars = sb + OFF_MISC;
    constexpr int NBOX = 44;
    auto issue = [&](int i) {
        const int st = i % M_STAGES;
        const uint32_t bar = bars + 8 * (B_AF + st), dst = sb + st * M_STAGE_BYTES;
        if (i < 28) {
            const int j = i < 24 ? (i >> 3) * 2 + (i & 1) : 6, q = i < 24 ? (i >> 1) & 3 : i & 3;
            mbar_expect(bar, 32768);
            tma2d(dst, (q & 2) ? mu : mg, part * 448 + j * 64, (q & 1) * 256, bar);
        } else {
            mbar_expect(bar, 28672);
            tma2d(dst, md, (((i - 28) >> 2) * 2 + (i & 1)) * 64, part * 448 + ((i >> 1) & 1) * 224, bar);
        }
    };
    __syncthreads();
    if (tid == 512) {
        const uint32_t ep = g_epoch[blockIdx.x] + 1;
        for (int i = 0; i < M_STAGES; i++) issue(i);
        g_epoch[blockIdx.x] = ep;
        cnt_wait(C_R, 128 * ep);
    }
    for (int i = tid; i < 4096; i += NTHR) ((uint32_t*)(smem + OFF_XSEL))[i] = 0;
    __syncthreads();
    unsigned long long b1 = 0, b2 = 0;
    if (tid < 512) {
        const float4 rv = __ldcg((const float4*)(g_r + tid * 4));
        const float rr[4] = {rv.x, rv.y, rv.z, rv.w};
#pragma unroll
        for (int j = 0; j < 4; j++) {
            uint32_t u = __float_as_uint(rr[j]);
            u = (u & 0x80000000u) ? ~u : (u | 0x80000000u);
            const unsigned long long k = ((unsigned long long)u << 32) | (uint32_t)(~(tid * 4 + j));
            if (k > b1) { b2 = b1; b1 = k; } else if (k > b2) b2 = k;
        }
    }
    auto merge = [&](int o) {
        const unsigned long long c1 = __shfl_xor_sync(~0u, b1, o), c2 = __shfl_xor_sync(~0u, b2, o);
        const unsigned long long hi = b1 > c1 ? b1 : c1, lo = b1 > c1 ? c1 : b1, s2 = b2 > c2 ? b2 : c2;
        b1 = hi; b2 = lo > s2 ? lo : s2;
    };
    for (int o = 16; o; o >>= 1) merge(o);
    unsigned long long* red = (unsigned long long*)(smem + OFF_MISC + 512);
    if (lane == 0) { red[warp * 2] = b1; red[warp * 2 + 1] = b2; }
    __syncthreads();
    b1 = red[(lane & 15) * 2]; b2 = red[(lane & 15) * 2 + 1];
    for (int o = 8; o; o >>= 1) merge(o);
    const int i0 = (int)(~(uint32_t)b1), i1 = (int)(~(uint32_t)b2);
    if (tid < 128) {
        const int t = tid >> 6, kc = tid & 63;
        *(uint4*)(smem + OFF_XSEL + kc * 128 + t * 16) = *(const uint4*)(P.x + (t ? i1 : i0) * D_ + kc * 8);
    }
    if (part == 0 && tid == 0) {
        g_sel[0] = i0; g_sel[1] = i1;
        g_sel[2] = __float_as_int(rbf(sigmoidf_(__ldcg(g_r + i0))));
        g_sel[3] = __float_as_int(rbf(sigmoidf_(__ldcg(g_r + i1))));
    }
    fence_async_s();
    __syncthreads();
    if (tid == 512) {
        for (int i = M_STAGES; i < NBOX; i++) {
            mbar_wait(bars + 8 * (B_AE + i % M_STAGES), (i / M_STAGES - 1) & 1);
            issue(i);
        }
    } else if (wg < 2) {
        const int w4 = warp & 3, g = lane >> 2;
        auto box = [&](float (&acc)[4], int i, int nk, uint32_t boff, int first) {
            const int st = i % M_STAGES;
            mbar_wait(bars + 8 * (B_AF + st), (i / M_STAGES) & 1);
            const uint64_t da = mkdesc(0, 8192, 1024, 1) + st * (M_STAGE_BYTES >> 4), db = mkdesc(0, 128, 256, 0) + (boff >> 4);
            reg_fence(acc);
            wg_fence();
            for (int k = 0; k < nk; k++) wg_ss_n8_at(acc, da + k * 128, db + k * 16, !(first && k == 0));
            wg_commit();
            wg_wait<0>();
            reg_fence(acc);
            named_sync(3 + wg, 128);
            if ((tid & 127) == 0) mbar_arrive(bars + 8 * (B_AE + st));
        };
#pragma unroll 1
        for (int j = wg; j < 7; j += 2) {
            float ag[4] = {0, 0, 0, 0}, au[4] = {0, 0, 0, 0};
            const int i = (j >> 1) * 8 + wg, di = j < 6 ? 2 : 1;
            box(ag, i, 16, OFF_XSEL, 1); box(ag, i + di, 16, OFF_XSEL + 4096, 0);
            box(au, i + 2 * di, 16, OFF_XSEL, 1); box(au, i + 3 * di, 16, OFF_XSEL + 4096, 0);
            if ((lane & 3) == 0) {
#pragma unroll
                for (int e = 0; e < 4; e++) {
                    const float gv = rbf(ag[e]), h = rbf(gv * sigmoidf_(gv)) * rbf(au[e]);
                    const int f = j * 64 + w4 * 16 + (e >> 1) * 8 + g;
                    *(__nv_bfloat16*)(smem + OFF_HSEL + (f >> 3) * 128 + (e & 1) * 16 + (f & 7) * 2) = __float2bfloat16_rn(h);
                }
            }
        }
        fence_async_s();
        named_sync(1, 256);
#pragma unroll 1
        for (int j = wg; j < 8; j += 2) {
            float a[4] = {0, 0, 0, 0};
            const int i = 28 + (j >> 1) * 4 + wg;
            box(a, i, 14, OFF_HSEL, 1); box(a, i + 2, 14, OFF_HSEL + 14 * 256, 0);
            if ((lane & 3) == 0) {
#pragma unroll
                for (int e = 0; e < 4; e++) g_y[(part * 2 + (e & 1)) * D_ + j * 64 + w4 * 16 + (e >> 1) * 8 + g] = a[e];
            }
        }
        named_sync(1, 256);
        if (tid == 0) { cnt_arrive(C_Y); TSTAMP(1); }
    }
}

__global__ void __launch_bounds__(NTHR, 1)
fused_kernel(const __grid_constant__ CUtensorMap mx, const __grid_constant__ CUtensorMap mkv, const __grid_constant__ CUtensorMap mq,
             const __grid_constant__ CUtensorMap mo, const __grid_constant__ CUtensorMap mout, const __grid_constant__ CUtensorMap mg,
             const __grid_constant__ CUtensorMap mu, const __grid_constant__ CUtensorMap md, const __grid_constant__ Params P) {
    extern __shared__ __align__(1024) uint8_t smem[];
    constexpr uint32_t sb = SBASE, bars = sb + OFF_MISC;
    const int tid = threadIdx.x, lane = tid & 31, warp = __shfl_sync(~0u, tid >> 5, 0), wg = warp >> 2, w4 = warp & 3;
    const int cta = blockIdx.x;
    volatile uint32_t* misc = (volatile uint32_t*)(smem + OFF_MISC + 320);
    volatile float* gate = (volatile float*)(smem + OFF_MISC + 512);
    const int nt = NTX, mt = MTX;
    const int rt = 2 * mt + (nt & 1), ct = nt >> 1;

    if (lane == 0) {
        if (warp == 16) {
            TSTAMP(0);
#pragma unroll
            for (int i = 0; i < 8; i++) mbar_init(bars + 8 * (B_AF + i), 1);
            fence_async_s();
            if (cta < 128) {
#pragma unroll
                for (int kc = 0; kc < 8; kc++) {
                    const uint32_t bar = bars + 8 * (B_AF + kc);
                    mbar_expect(bar, 32768);
                    tma2d(sb + off_x(kc), &mx, kc * 64, mt * 128, bar);
                    if (kc < 6) tma3d(sb + off_w(kc), &mkv, nt * 64, kc * 64, 1, bar);
                }
                TSTAMP(15);
            }
        } else if (wg < 4) {
            const uint32_t c = cta < 128 ? (uint32_t)(BAR_CNT >> (warp * 4)) & 15 : 0;
            mbar_init(bars + 8 * (8 + 2 * warp), c + 1);
            mbar_init(bars + 8 * (9 + 2 * warp), c + 1);
            fence_async_s();
            if ((uint32_t)__cvta_generic_to_shared(smem) != SBASE) __trap();
        }
    }
    __syncwarp();
    if (cta >= 128) {
        mod_cta(smem, sb, P, &mg, &mu, &md);
        return;
    }

    if (wg == 4) {
        const uint32_t ep = g_epoch[cta] + 1;
        named_sync(7, NTHR);
        if (warp == 17) {
        if (lane == 0) {
            mbar_wait(bars + 8 * B_KVP, 0);
            TSTAMP(7);
            cnt_arrive(C_KV + nt);
            cnt_wait(C_R, 128 * ep);
            cnt_wait(C_KV + nt, 16 * ep);
            mbar_wait(bars + 8 * B_AFREE, 0);
        }
        __syncwarp();
        ((float4*)gate)[lane] = __ldcg((const float4*)(g_g + mt * 128) + lane);
        {
            const uint4 v = __ldcg((const uint4*)(g_mx + nt * 128) + lane);
            uint32_t m = max(max(v.x, v.y), max(v.z, v.w));
            m = max(m, __shfl_xor_sync(~0u, m, 1));
            m = max(m, __shfl_xor_sync(~0u, m, 2));
            uint32_t qn = misc[8 + lane];
            qn = max(qn, __shfl_xor_sync(~0u, qn, 4));
            qn = max(qn, __shfl_xor_sync(~0u, qn, 8));
            qn = max(qn, __shfl_xor_sync(~0u, qn, 16));
            const float k2 = __uint_as_float(__shfl_sync(~0u, m, (lane & 3) * 4)), vm = __uint_as_float(__shfl_sync(~0u, m, 16 + (lane & 3) * 4));
            const float q2 = __uint_as_float(qn);
            if (lane < 4) misc[4 + lane] = q2 * k2 <= BOUND_MAX * BOUND_MAX && q2 <= 65536.f && k2 <= 65536.f && vm >= 0.03125f ? 0x43800000u : 0x7f800000u;
        }
        __syncwarp();
        if (lane == 0) {
            mbar_arrive(bars + 8 * B_CHK);
            l2_prefetch(P.wg + cta * 7168, 14336); l2_prefetch(P.wu + cta * 7168, 14336); l2_prefetch(P.wd + cta * 7168, 14336);
            l2_prefetch(P.wo + cta * 2048, 4096);
            mbar_wait(bars + 8 * (B_KF + 3), 0);
            mbar_expect(bars + 8 * B_WOE, 65536);
            for (int j = 0; j < 2; j++) tma4d(sb + OFF_WOE + j * 32768, &mo, ct * 128 + j * 64, 0, 0, 0, bars + 8 * B_WOE);
        }
        __syncwarp();
        }
        if (warp == 16) {
        auto kv_stage = [&](int s) {
            const uint32_t bar = bars + 8 * (B_KF + (s & 3)), dst = sb + (s & 3) * SLOT;
            const uint8_t* src = g_kv + (nt * 16 + s) * 32768;
            mbar_expect(bar, 32768);
            bulk_ld(dst, src, 16384, bar);
            bulk_ld(dst + 18432, src + 16384, 16384, bar);
        };
        if (lane == 0) {
            g_epoch[cta] = ep;
#pragma unroll 1
            for (int i = 0; i < 6; i++) {
                mbar_wait(bars + 8 * (B_AE + i), 0);
                if (i < 2) tma3d(sb + off_w(i), &mkv, nt * 64, (6 + i) * 64, 1, bars + 8 * (B_AF + 6 + i));
                else {
                    mbar_expect(bars + 8 * (B_QF + i - 2), 16384);
                    tma2d(sb + off_w(i), &mq, nt * 64, (i - 2) * 128, bars + 8 * (B_QF + i - 2));
                }
            }
            mbar_wait(bars + 8 * B_GO, 0);
            TSTAMP(12);
            if (mt < 8) cnt_arrive(C_U + nt);
            if (HOLD) mbar_arrive(bars + 8 * B_HOLD);
            TSTAMP(3);
            cnt_wait(C_U + nt, 8 * ep);
            TSTAMP(4);
            fence_async_g();
            kv_stage(0);
            mbar_wait(bars + 8 * B_AFREE, 0);
            for (int s = 1; s <= GOJ / 4; s++) kv_stage(s);
            cnt_wait(C_KV + nt, 16 * ep);
            fence_async_g();
            for (int s = GOJ / 4 + 1; s < 4; s++) kv_stage(s);
            TSTAMP(19);
#pragma unroll 1
            for (int s = 4; s < 16; s++) {
                mbar_wait(bars + 8 * (B_KF + ((s - 2) & 3)), ((s - 2) >> 2) & 1);
                if (s == 8) mbar_wait(bars + 8 * B_CHK, 0);
                kv_stage(s);
            }
            TSTAMP(18);
            mbar_arrive(bars + 8 * B_KF);
            mbar_wait(bars + 8 * B_OP, 0);
            cnt_arrive(C_O + mt);
            cnt_wait(C_Y, 4 * ep);
        }
        __syncwarp();
        }
        named_sync(9, 128);
        float acc[64];
        {
            const int4 sel = __ldcg((const int4*)g_sel);
            uint32_t* bsel = (uint32_t*)(smem + OFF_BSEL);
            if ((sel.x >> 6) == rt || (sel.y >> 6) == rt) {
                const int t = w4 >> 1, c = ct * 128 + (tid & 63) * 2;
                const float rs = __int_as_float(t ? sel.w : sel.z);
                const uint32_t xv = *(const uint32_t*)(P.x + (t ? sel.y : sel.x) * D_ + c);
                float y0 = 0.f, y1 = 0.f;
#pragma unroll
                for (int pp = 0; pp < 4; pp++) {
                    const float2 v = __ldcg((const float2*)(g_y + (pp * 2 + t) * D_ + c));
                    y0 += v.x; y1 += v.y;
                }
                bsel[tid - 512] = pack_b2(blo(xv) + rbf(rbf(y0) * rs), bhi(xv) + rbf(rbf(y1) * rs));
                named_sync(9, 128);
            }
#pragma unroll
            for (int h = 0; h < 2; h++) {
                const int lr = (nt & 1) * 64 + w4 * 16 + (lane >> 2) + 8 * h, r = mt * 128 + lr;
                const float g = 1.f - gate[lr];
                const uint32_t* xp = (r == sel.x ? bsel : r == sel.y ? bsel + 64 : (const uint32_t*)(P.x + r * D_ + ct * 128)) + (lane & 3);
#pragma unroll
                for (int j = 0; j < 16; j++) { const uint32_t xv = xp[j * 4]; acc[4 * j + 2 * h] = g * blo(xv); acc[4 * j + 2 * h + 1] = g * bhi(xv); }
            }
        }
        __syncwarp();
        if (tid == 512) {
            TSTAMP(17);
            mbar_wait(bars + 8 * (B_KF + 2), 1);
            cnt_wait(C_O + mt, 8 * ep);
            fence_async_g();
            mbar_expect(bars + 8 * B_OE, 32768);
            bulk_ld(sb, g_o + rt * 65536, 32768, bars + 8 * B_OE);
            mbar_expect(bars + 8 * B_WL, 65536);
            for (int j = 0; j < 2; j++) {
                mbar_wait(bars + 8 * (B_KF + 3 - 3 * j), 1 - j);
                tma4d(sb + (1 + j) * SLOT, &mo, ct * 128 + j * 64, 0, 1, 0, bars + 8 * B_WL);
            }
            mbar_wait(bars + 8 * B_TRG, 0);
            TSTAMP(16);
        }
        __syncwarp();
        named_sync(9, 128);
        mbar_wait_u(bars + 8 * B_WOE, 0);
        mbar_wait_u(bars + 8 * B_OE, 0);
        reg_fence(acc);
        wg_fence();
#pragma unroll
        for (int k = 0; k < 16; k++) wg_ss_n128_bt(acc, mkdesc(k * 2048, 128, 256, 0), mkdesc(OFF_WOE + k * 2048, 32768, 1024, 1), 1);
        wg_commit();
        mbar_wait_u(bars + 8 * B_WL, 0);
        if (tid == 512) TSTAMP(8);
#pragma unroll
        for (int c = 3; c >= 0; c--) {
            mbar_wait_u(bars + 8 * (B_OL + c), 0);
            if (tid == 512 && c == 2) TSTAMP(13);
            if (tid == 512 && c == 0) TSTAMP(9);
            wg_fence();
#pragma unroll
            for (int i = 0; i < 4; i++)
                wg_ss_n128_bt(acc, mkdesc(off_ol(c) + i * 2048, 128, 256, 0), mkdesc(SLOT + ((c & 1) * 8 + 2 * i + (c >> 1)) * 2048, SLOT, 1024, 1), 1);
            wg_commit();
        }
        wg_wait<0>();
        reg_fence(acc);
        if (tid == 512) TSTAMP(10);
        const uint32_t stg = sb + 3 * SLOT + 18432 + w4 * 4096, sa = stg + (lane & 15) * 128;
#pragma unroll
        for (int j = 0; j < 16; j += 2) {
            uint32_t v[4];
#pragma unroll
            for (int e = 0; e < 4; e++) v[e] = pack_b2(acc[4 * j + 2 * e], acc[4 * j + 2 * e + 1]);
            asm volatile("stmatrix.sync.aligned.m8n8.x4.shared.b16 [%0], {%1, %2, %3, %4};"
                         ::"r"(sa + (j >> 3) * 2048 + ((((j & 7) + (lane >> 4)) ^ (lane & 7)) << 4)), "r"(v[0]), "r"(v[1]), "r"(v[2]), "r"(v[3]) : "memory");
        }
        fence_async_s();
        __syncwarp();
        if (lane < 2) {
            asm volatile("cp.async.bulk.tensor.2d.global.shared::cta.bulk_group [%0, {%1, %2}], [%3];"
                         ::"l"(&mout), "r"(ct * 128 + lane * 64), "r"(rt * 64 + w4 * 16), "r"(stg + lane * 2048) : "memory");
            asm volatile("cp.async.bulk.commit_group;" ::: "memory");
            asm volatile("cp.async.bulk.wait_group.read 0;" ::: "memory");
            if (tid == 512) TSTAMP(11);
        }
        return;
    }

    uint4 qa, qb;
    if (wg < 2) {
        if (wg == 0) {
            *(uint4*)(smem + 16384 + tid * 16) = make_uint4(0x3c003c00u, 0x3c003c00u, 0x3c003c00u, 0x3c003c00u);
            fence_async_s();
        }
        const int st = w4 & 1, cg = mt & 7;
        uint8_t* const dst = g_kv + ((nt * 2 + (w4 >> 1)) * 8 + (mt >> 3) * 4) * 32768 + st * 16384 + lane * 4 + (wg ? cg * 128 : st * 6144 + cg * 256);
        const int o00 = st ? 0 : 12288;
        auto kslot = [&](int j, int h) { return (uint32_t*)(dst + (j >> 2) * 32768 + ((j >> 1) & 1) * 6144 + (j & 1) * 2048 + h * 128); };
        auto vslot = [&](int j, int h) { return (uint32_t*)(dst + (j >> 2) * 32768 + ((j & 2) ? 4096 + h * 6144 : o00 + h * 2048) + (j & 1) * 1024); };
        named_sync(7, NTHR);
        float acc[64];
#pragma unroll
        for (int kc = 0; kc < 8; kc++) {
            mbar_wait_u(bars + 8 * (B_AF + kc), 0);
            if (kc == 0 && tid == 0) TSTAMP(1);
            const uint64_t da = mkdesc(off_w(kc % 6), 8192, 1024, 1) + wg * 512, db = mkdesc(off_x(kc), 16, 1024, 1);
            wg_fence();
#pragma unroll
            for (int kk = 0; kk < 4; kk++) wg_ss_n128_at(acc, da + kk * 128, db + kk * 2, kc + kk > 0);
            wg_commit();
            if (kc >= 1 && kc <= 6) {
                wg_wait<1>();
                if ((tid & 127) == 0) mbar_arrive(bars + 8 * (B_AE + kc - 1));
            }
        }
        wg_wait<0>();
        reg_fence(acc);
        if (tid == 0) TSTAMP(2);
        uint32_t mxv;
        const bool urgent = mt < 8 && w4 < 2;
        auto go = [&]() {
            __syncwarp();
            if (lane == 0) mbar_arrive(bars + 8 * B_GO);
            if (HOLD && mt < 8) mbar_wait_u(bars + 8 * B_HOLD, 0);
        };
        if (QGO < 0) asm volatile("bar.arrive 8, 512;" ::: "memory");
        if (!urgent) go();
        if (wg == 0) {
#pragma unroll
            for (int j = 0; j < 16; j++) {
#pragma unroll
                for (int h = 0; h < 2; h++) {
                    const int i = 4 * j + 2 * h;
                    *kslot(j, h) = j ? pack_h2(acc[i] - acc[i - 4], acc[i + 1] - acc[i - 3]) : pack_h2(acc[i], acc[i + 1]);
                }
                if (j == GOJ && urgent) go();
                if (j == QGO) asm volatile("bar.arrive 8, 512;" ::: "memory");
            }
            uint32_t n[16];
#pragma unroll
            for (int j = 0; j < 16; j++) n[j] = pack_b2(acc[4 * j] * acc[4 * j] + acc[4 * j + 2] * acc[4 * j + 2], acc[4 * j + 1] * acc[4 * j + 1] + acc[4 * j + 3] * acc[4 * j + 3]);
            auto fold = [&](auto oc) {
                constexpr int o = decltype(oc)::v;
                const bool up = lane & (2 * o);
#pragma unroll
                for (int i = 0; i < o; i++) {
                    const uint32_t t = __shfl_xor_sync(~0u, up ? n[i] : n[i + o], 2 * o), k = up ? n[i + o] : n[i];
                    asm("add.bf16x2 %0, %1, %2;" : "=r"(n[i]) : "r"(t), "r"(k));
                }
            };
            fold(IC<8>()); fold(IC<4>()); fold(IC<2>());
            mxv = max(max(n[0] << 16, n[0] & 0xffff0000u), max(n[1] << 16, n[1] & 0xffff0000u));
        } else {
            float mm = 0.f;
#pragma unroll
            for (int j = 0; j < 16; j++) {
#pragma unroll
                for (int h = 0; h < 2; h++) *vslot(j, h) = pack_h2(acc[4 * j + 2 * h], acc[4 * j + 2 * h + 1]);
                if (j == GOJ && urgent) go();
                if (j == QGO) asm volatile("bar.arrive 8, 512;" ::: "memory");
            }
#pragma unroll
            for (int i = 0; i < 64; i++) mm = fmaxf(mm, fabsf(acc[i]));
            mxv = __float_as_uint(mm);
        }
        mxv = __reduce_max_sync(~0u, mxv);
        if (lane == 0) { g_mx[nt * 128 + warp * 16 + mt] = __uint_as_float(mxv); mbar_arrive(bars + 8 * B_KVP); }
        named_sync(1, 512);
        const uint4* qx = (const uint4*)(smem + off_x(0) + wg * 8192) + (tid & 127);
        qa = qx[0]; qb = qx[128];
    } else {
        {
            const int row0 = cta * 16 + (warp - 8) * 2;
            uint4 xv[2][2], wr[2], wgt[2];
#pragma unroll
            for (int c = 0; c < 2; c++) {
#pragma unroll
                for (int r = 0; r < 2; r++) xv[r][c] = *(const uint4*)(P.x + (row0 + r) * D_ + c * 256 + lane * 8);
                wr[c] = *(const uint4*)(P.w_r + c * 256 + lane * 8);
                wgt[c] = *(const uint4*)(P.gate_w + c * 256 + lane * 8);
            }
            named_sync(7, NTHR);
                auto dot8 = [](uint4 a, uint4 b) {
                return blo(a.x) * blo(b.x) + bhi(a.x) * bhi(b.x) + blo(a.y) * blo(b.y) + bhi(a.y) * bhi(b.y) +
                       blo(a.z) * blo(b.z) + bhi(a.z) * bhi(b.z) + blo(a.w) * blo(b.w) + bhi(a.w) * bhi(b.w);
            };
#pragma unroll
            for (int r = 0; r < 2; r++) {
                float a = dot8(xv[r][0], wr[0]) + dot8(xv[r][1], wr[1]), b = dot8(xv[r][0], wgt[0]) + dot8(xv[r][1], wgt[1]);
#pragma unroll
                for (int o = 16; o; o >>= 1) { a += __shfl_xor_sync(~0u, a, o); b += __shfl_xor_sync(~0u, b, o); }
                if (lane == 0) { g_r[row0 + r] = rbf(a); g_g[row0 + r] = sigmoidf_(b); }
            }
#pragma unroll
            for (int i = 0; i < 2; i++)
                *((uint4*)(g_o + (2 * mt + i) * 65536 + 32768 + nt * 4096) + (tid - 256)) = make_uint4(~0u, ~0u, ~0u, ~0u);
            named_sync(2, 256);
            if (tid == 256) cnt_arrive(C_R);
            __syncwarp();
        }
        float acc[32];
        named_sync(8, 512);
#pragma unroll
        for (int kc = 0; kc < 8; kc++) {
            if (!(kc & 1)) mbar_wait_u(bars + 8 * (B_QF + (kc >> 1)), 0);
            mbar_wait_u(bars + 8 * (B_AF + kc), 0);
            const uint64_t da = mkdesc(off_x(kc), 16, 1024, 1) + (wg - 2) * 512, db = mkdesc(off_w(2 + (kc >> 1)) + (kc & 1) * 8192, 8192, 1024, 1);
            wg_fence();
#pragma unroll
            for (int kk = 0; kk < 4; kk++) wg_ss_n64_bt(acc, da + kk * 2, db + kk * 128, kc + kk > 0);
            wg_commit();
        }
        wg_wait<0>();
        reg_fence(acc);
        if (tid == 256) TSTAMP(14);
#pragma unroll
        for (int i = 0; i < 32; i++) acc[i] *= QSCALE;
        auto frag = [&](int h) {
            return make_uint4(pack_h2(acc[8 * h], acc[8 * h + 1]), pack_h2(acc[8 * h + 2], acc[8 * h + 3]),
                              pack_h2(acc[8 * h + 4], acc[8 * h + 5]), pack_h2(acc[8 * h + 6], acc[8 * h + 7]));
        };
        named_sync(3 + wg, 128);
        uint4* qx = (uint4*)(smem + off_x(0) + (wg - 2) * 8192) + (tid & 127);
        qx[0] = frag(0); qx[128] = frag(2);
        if (warp == 15) *(float*)(smem + OFF_INIT + lane * 4) = (PAT >> (lane >> 1) * 4 & 15) == 0 ? init_of_t(0) : (PAT >> (lane >> 1) * 4 & 15) == 2 ? init_of_t(2) : init_of_t(3);
        qa = frag(1); qb = frag(3);
        named_sync(1, 512);
#pragma unroll
        for (int i = 1; i < 4; i++) *(uint2*)(smem + i * SLOT + 16384 + (tid - 256) * 8) = make_uint2(0x3c003c00u, 0x3c003c00u);
        float nrm[8];
#pragma unroll
        for (int h = 0; h < 4; h++) {
            const float* k = &acc[8 * h];
            nrm[2 * h] = k[0] * k[0] + k[1] * k[1] + k[4] * k[4] + k[5] * k[5];
            nrm[2 * h + 1] = k[2] * k[2] + k[3] * k[3] + k[6] * k[6] + k[7] * k[7];
        }
        const bool o2 = lane & 2, o1 = lane & 1;
        float u[4];
#pragma unroll
        for (int i = 0; i < 4; i++) u[i] = (o2 ? nrm[4 + i] : nrm[i]) + __shfl_xor_sync(~0u, o2 ? nrm[i] : nrm[4 + i], 2);
        const float a = (o1 ? u[2] : u[0]) + __shfl_xor_sync(~0u, o1 ? u[0] : u[2], 1);
        const float b = (o1 ? u[3] : u[1]) + __shfl_xor_sync(~0u, o1 ? u[1] : u[3], 1);
        uint32_t m = max(__float_as_uint(a), __float_as_uint(b));
        m = max(m, __shfl_xor_sync(~0u, m, 4));
        m = max(m, __shfl_xor_sync(~0u, m, 8));
        m = max(m, __shfl_xor_sync(~0u, m, 16));
        if (lane < 4) misc[8 + (warp - 8) * 4 + lane] = m;
        fence_async_s();
        __syncwarp();
        if (lane == 0) mbar_arrive(bars + 8 * B_AFREE);
    }

    const int st = wg >> 1;
    uint8_t* const odst = g_o + (2 * mt + (wg & 1)) * 65536 + (nt * 2 + st) * 2048;
    uint32_t fail = 0;
    {
        float s[32];
        uint32_t o[6], o2[6];
        uint32_t q0 = qa.x, q1 = qa.y, q2 = qa.z, q3 = qa.w;
        uint32_t c3c = 0x3c003c00u;
        asm volatile("" : "+r"(c3c));
        const uint64_t dk0 = mkdesc(0, 128, 256, 0) + st * (24576 >> 4);
        const uint64_t dv0 = mkdesc(12288, 128, 2048, 0) + st * (4096 >> 4), dw0 = mkdesc(4096, 128, 6144, 0) + st * (12288 >> 4);
        const bool sig = (tid & 127) == 0;
        const uint8_t* op = odst + w4 * 512 + lane * 4;
        uint32_t ga = sb + OFF_MISC + 512 + ((wg & 1) * 64 + w4 * 16 + (lane >> 2)) * 4, par = 0;
        asm volatile("" : "+l"(op), "+r"(ga));
        init_s(s);
        if (sig) mbar_arrive(bars + 8 * B_KF);
        mbar_wait_u(bars + 8 * B_KF, 0);
        if (tid == 0) { TSTAMP(5); CSTAMP(30); }
        wg_fence();
        wg_rs_qk(s, q0, q1, q2, q3, dk0);
        wg_commit();
        wg_wait<0>();
        reg_fence(s);
#define ATT_BLOCK(I, U, DN)                                                                                       \
    {                                                                                                             \
        uint32_t p[16], ok;                                                                                       \
        if (U == 3) { if (I == 3) par ^= 1; ok = mbar_probe(nb, par); }                                           \
        ExpLoop<0>::run(s, p, c3c);                                                                               \
        if (FL8 && I == 2 && U == 0) {                                                                            \
            wg_wait<0>(); reg_fence(o);                                                                           \
            _Pragma("unroll") for (int i = 0; i < 6; i++) o2[i] = hfma2(o[i], 0x38003800u, o2[i]);                \
        }                                                                                                         \
        if (I == 3 && U == 3) {                     \
            init_s(s);                                                                                            \
            if (seg & 1) { q0 = qb.x; q1 = qb.y; q2 = qb.z; q3 = qb.w; }                                          \
        }                                                                                                         \
        if (U == 3) mbar_finish(ok, nb, par);                                                                     \
        wg_fence();                                                                                               \
        wg_rs_qk(s, q0, q1, q2, q3, DN);                                                                          \
        const uint64_t dp = (U < 2 ? dv : dw) + (U & 1) * 64;                                                     \
        if (U == 0 && (I == 0 || (FL8 && I == 2))) wg_rs_pv0(o, p[0], p[1], p[2], p[3], dp);                      \
        else wg_rs_pv(o, p[0], p[1], p[2], p[3], dp);                                                             \
        wg_rs_pv(o, p[4], p[5], p[6], p[7], dp + 16);                                                             \
        wg_commit();                                                                                              \
        wg_rs_pv(o, p[8], p[9], p[10], p[11], dp + 32);                                                           \
        wg_rs_pv(o, p[12], p[13], p[14], p[15], dp + 48);                                                         \
        wg_commit();                                                                                              \
        wg_wait<(I == 3 && U == 3) ? 0 : 1>();                                                                    \
        if (U == ARR && sig) mbar_arrive(nb);                                                                     \
        reg_fence(s);                                                                                             \
    }
#define ATT_STAGE(I)                                                                                              \
    {                                                                                                             \
        const uint64_t dk = dk0 + I * (SLOT >> 4), dv = dv0 + I * (SLOT >> 4), dw = dw0 + I * (SLOT >> 4);        \
        constexpr uint32_t nb = bars + 8 * (B_KF + ((I + 1) & 3));                                                \
        ATT_BLOCK(I, 0, dk + 128)                                                                                 \
        ATT_BLOCK(I, 1, dk + 384)                                                                                 \
        ATT_BLOCK(I, 2, dk + 512)                                                                                 \
        ATT_BLOCK(I, 3, dk0 + ((I + 1) & 3) * (SLOT >> 4))                                                        \
    }
#pragma unroll
        for (int i = 0; i < 6; i++) o2[i] = 0;
#pragma unroll 1
        for (int seg = 0; seg < 4; seg++) {
            ATT_STAGE(0) ATT_STAGE(1) ATT_STAGE(2) ATT_STAGE(3)
            reg_fence(o);
#pragma unroll
            for (int i = 0; i < 6; i++) o2[i] = hfma2(o[i], 0x38003800u, o2[i]);
            if (seg & 1) {
                float g0, g1, lmin;
                asm volatile("ld.shared.f32 %0, [%3];\nld.shared.f32 %1, [%3 + 32];\nld.shared.f32 %2, [%4];"
                             : "=f"(g0), "=f"(g1), "=f"(lmin) : "r"(ga), "r"(sb + OFF_MISC + 336 + 4 * (seg - 1 + st)));
                uint32_t w[4];
                bool ok;
                auto fin = [&](auto oc) {
                    constexpr int a = decltype(oc)::v;
                    const float l0 = h2f(o2[4 - 2 * a]).x, l1 = h2f(o2[5 - 2 * a]).x;
                    g0 *= frcp(l0); g1 *= frcp(l1);
#pragma unroll
                    for (int i = 0; i < 4; i++) {
                        const float2 v = h2f(o2[a + i]);
                        w[i] = pack_b2(v.x * ((i & 1) ? g1 : g0), v.y * ((i & 1) ? g1 : g0));
                    }
                    ok = l0 >= lmin && l1 >= lmin;
                };
                if (st) fin(IC<2>()); else fin(IC<0>());
                uint32_t z = 0;
#pragma unroll
                for (int i = 0; i < 6; i++) { z = hfma2(o2[i], 0, z); o2[i] = 0; }
                if (!__all_sync(~0u, ok && z == 0)) fail |= seg + 1;
                else if (seg == 3) *(uint4*)(op + 32768 + lane * 12) = make_uint4(w[0], w[1], w[2], w[3]);
                else {
#pragma unroll
                    for (int i = 0; i < 4; i++) ((uint32_t*)op)[(i >> 1) * 32 + (i & 1) * 64] = w[i];
                    __syncwarp();
                    if (lane == 0) mbar_arrive(bars + 8 * B_OP);
                }
            }
        }
        fail >>= 1;
        if (tid == 0) { TSTAMP(6); CSTAMP(31); }
    }
    if (st == TRGST && lane == 0) mbar_arrive(bars + 8 * B_TRG);
    if (wg_any(3 + wg, fail)) {
        for (int ps = 0; ps < 2; ps++)
            if (wg_any(3 + wg, (fail >> ps) & 1)) {
                attn_slow(smem + OFF_STG + (st ? (wg & 1) * 8192 : 16384 + wg * 4096), P.x, P.wqkv, nt * 4 + 2 * ps + st, 2 * mt + (wg & 1), odst + ps * 32768, ps,
                          gate[(wg & 1) * 64 + (tid & 63)], 3 + wg);
                if (ps == 0 && (fail & 1) && lane == 0) mbar_arrive(bars + 8 * B_OP);
            }
    }
    {
        uint4 f[4];
        const int k0 = (wg & 1) * 8 + st;
        const uint4* src = (const uint4*)(g_o + rt * 65536 + 32768 + k0 * 2048) + (tid & 127);
        auto ldf = [&](int i) {
            asm volatile("ld.relaxed.gpu.global.v4.u32 {%0, %1, %2, %3}, [%4];" : "=r"(f[i].x), "=r"(f[i].y), "=r"(f[i].z), "=r"(f[i].w) : "l"(src + i * 256) : "memory");
        };
#pragma unroll
        for (int i = 0; i < 4; i++) ldf(i);
        if (st == 0) named_sync(10, 256);
        for (uint32_t n = 0;; n++) {
            bool any = false;
#pragma unroll
            for (int i = 0; i < 4; i++)
                if (f[i].x == ~0u || f[i].y == ~0u || f[i].z == ~0u || f[i].w == ~0u) { ldf(i); any = true; }
            if (!__any_sync(~0u, any)) break;
            if (n > 0x800000u) __trap();
        }
        const uint32_t fa = sb + off_ol(wg) + w4 * 512 + (lane & 8) * 32 + (lane >> 4) * 128 + (lane & 7) * 16;
#pragma unroll
        for (int i = 0; i < 4; i++)
            asm volatile("stmatrix.sync.aligned.m8n8.x4.shared.b16 [%0], {%1, %2, %3, %4};"
                         ::"r"(fa + i * 2048), "r"(f[i].x), "r"(f[i].y), "r"(f[i].z), "r"(f[i].w) : "memory");
        fence_async_s();
        __syncwarp();
        if (lane == 0) mbar_arrive(bars + 8 * (B_OL + wg));
    }
}

typedef CUresult (*EncodeFn)(CUtensorMap*, CUtensorMapDataType, cuuint32_t, void*, const cuuint64_t*, const cuuint64_t*, const cuuint32_t*,
                             const cuuint32_t*, CUtensorMapInterleave, CUtensorMapSwizzle, CUtensorMapL2promotion, CUtensorMapFloatOOBfill);

void make_map(EncodeFn fn, CUtensorMap* m, const void* p, int rank, const cuuint64_t* dims, const cuuint64_t* strides, const cuuint32_t* box) {
    cuuint32_t es[4] = {1, 1, 1, 1};
    fn(m, CU_TENSOR_MAP_DATA_TYPE_BFLOAT16, rank, (void*)p, dims, strides, box, es, CU_TENSOR_MAP_INTERLEAVE_NONE, CU_TENSOR_MAP_SWIZZLE_128B,
       CU_TENSOR_MAP_L2_PROMOTION_L2_128B, CU_TENSOR_MAP_FLOAT_OOB_FILL_NONE);
}
void make_map2(EncodeFn fn, CUtensorMap* m, const void* p, int rows, int cols, int box_rows) {
    cuuint64_t dims[2] = {(cuuint64_t)cols, (cuuint64_t)rows}, strides[1] = {(cuuint64_t)cols * 2};
    cuuint32_t box[2] = {64, (cuuint32_t)box_rows};
    make_map(fn, m, p, 2, dims, strides, box);
}

}

extern "C" void kernel_launch(void* const* d_in, const int* in_sizes, int n_in, void* d_out, int out_size) {
    static EncodeFn fn = nullptr;
    if (!fn) {
        void* f = nullptr;
        cudaDriverEntryPointQueryResult qr;
        cudaGetDriverEntryPoint("cuTensorMapEncodeTiled", &f, cudaEnableDefault, &qr);
        fn = (EncodeFn)f;
        cudaFuncSetAttribute(fused_kernel, cudaFuncAttributeMaxDynamicSharedMemorySize, SMEM_BYTES);
    }
    CUtensorMap mx, mkv, mq, mo, mout, mg, mu, md;
    make_map2(fn, &mx, d_in[0], S_, D_, 128);
    {
        cuuint64_t dims[3] = {512, 512, 3}, strides[2] = {3072, 1024};
        cuuint32_t box[3] = {64, 64, 2};
        make_map(fn, &mkv, d_in[1], 3, dims, strides, box);
    }
    make_map2(fn, &mq, d_in[1], D_, 3 * D_, 128);
    {
        cuuint64_t dims[4] = {512, 32, 2, 8}, strides[3] = {1024, 32768, 65536};
        cuuint32_t box[4] = {64, 32, 1, 8};
        make_map(fn, &mo, d_in[2], 4, dims, strides, box);
    }
    make_map2(fn, &mout, d_out, S_, D_, 16);
    make_map2(fn, &mg, d_in[5], D_, F_, 256);
    make_map2(fn, &mu, d_in[6], D_, F_, 256);
    make_map2(fn, &md, d_in[7], F_, D_, 224);
    Params P;
    P.x = (const __nv_bfloat16*)d_in[0];
    P.wqkv = (const __nv_bfloat16*)d_in[1];
    P.w_r = (const __nv_bfloat16*)d_in[4];
    P.gate_w = (const __nv_bfloat16*)d_in[8];
    P.wg = (const __nv_bfloat16*)d_in[5];
    P.wu = (const __nv_bfloat16*)d_in[6];
    P.wd = (const __nv_bfloat16*)d_in[7];
    P.wo = (const __nv_bfloat16*)d_in[2];
    fused_kernel<<<NCTA, NTHR, SMEM_BYTES, cudaStreamPerThread>>>(mx, mkv, mq, mo, mout, mg, mu, md, P);
}
```

```cpp
#include <cuda_runtime.h>
#include <cuda_bf16.h>
#include <cuda_fp16.h>
#include <cuda.h>
#include <stdint.h>

namespace {

constexpr int S_ = 2048, D_ = 512, F_ = 1792;
constexpr int NCTA = 132, NTHR = 640;
constexpr uint32_t SBASE = 0x400;
constexpr int SMEM_BYTES = 232448;

__host__ __device__ constexpr int off_w(int i) { return i == 0 ? 0 : 2048 + i * 16384; }
__host__ __device__ constexpr int off_x(int c) { return 100352 + (7 - c) * 16384; }
constexpr int SLOT = 34816;
constexpr int OFF_WOE = 4 * SLOT;
constexpr int OFF_STG = OFF_WOE + 65536;
__host__ __device__ constexpr int off_ol(int c) { return (c < 2 ? 3 * SLOT : OFF_STG) + (c & 1) * 8192; }
__host__ __device__ constexpr int off_q(int ps, int wg) {
    return OFF_STG + (ps == 0 ? 12288 - (wg & 1) * 8192 + (wg >> 1) * 2048 : wg >= 2 ? (wg & 1) * 8192 : 16384 + wg * 2048);
}
constexpr int OFF_BSEL = OFF_STG + 24576;
constexpr int OFF_INIT = OFF_BSEL + 512;
constexpr int OFF_MISC = 231424;
constexpr int M_STAGES = 6, M_STAGE_BYTES = 32768;
constexpr int OFF_XSEL = M_STAGES * M_STAGE_BYTES, OFF_HSEL = OFF_XSEL + 8192;
constexpr int B_AF = 0, B_AE = 8, B_QF = 14, B_AFREE = 18, B_KVP = 19, B_KF = 20, B_WL = 24, B_OE = 25, B_WOE = 26, B_K0 = 27, B_OP = 28, B_OL = 30, B_TRG = 35, B_GO = 36, B_HOLD = 38, B_CHK = 39;
constexpr unsigned long long BAR_CNT = 0x07000f0044700111ull;
constexpr int C_KV = 0, C_O = 8, C_R = 40, C_Y = 41, C_U = 42, NCNT = 50;

#define EXP_PAT 0x3333303033333030ull
constexpr unsigned long long PAT = EXP_PAT;
__host__ __device__ constexpr int pat_of(int i) { return (int)((PAT >> (4 * i)) & 15); }
constexpr float U0 = 12.f, OFF_C = 1.585497f, OFF_E = 2.083684f;
__host__ __device__ constexpr float init_of_t(int t) {
    return t == 0 ? U0 - 15.f + OFF_E : t == 2 ? 32.f + U0 + OFF_E - OFF_C : 32.f + U0;
}
#define TRGN 3
#define NPV 1
#define QA 0
#define GOJ 7
#define ARR 0
constexpr float BOUND_MAX = 19.2f;
constexpr float QSCALE = 0.25f * 1.4426950408889634f;

#define NTX ((cta & 3) | (cta >> 6 & 1) << 2)
#define MTX (cta >> 2 & 15)
__device__ __align__(1024) uint8_t g_kv[8 * 2 * 8 * 32768];
__device__ __align__(1024) uint8_t g_o[32 * 65536];
__device__ __align__(16) float g_mx[8 * 128];
__device__ __align__(16) float g_r[S_];
__device__ __align__(16) float g_g[S_];
__device__ __align__(16) float g_y[4 * 2 * D_];
__device__ __align__(16) int g_sel[4];
__device__ uint32_t g_cnt[NCNT * 32];
__device__ uint32_t g_epoch[NCTA];
#define TSTAMP(i)
#define CSTAMP(i)

__device__ __forceinline__ void wg_ss_n128_at(float (&d)[64], uint64_t da, uint64_t db, int acc) {
  asm volatile("{\n.reg .pred p;\nsetp.ne.b32 p, %66, 0;\n"
      "wgmma.mma_async.sync.aligned.m64n128k16.f32.bf16.bf16 {%0,%1,%2,%3,%4,%5,%6,%7,%8,%9,%10,%11,%12,%13,%14,%15,%16,%17,%18,%19,%20,%21,%22,%23,"
      "%24,%25,%26,%27,%28,%29,%30,%31,%32,%33,%34,%35,%36,%37,%38,%39,%40,%41,%42,%43,%44,%45,%46,%47,"
      "%48,%49,%50,%51,%52,%53,%54,%55,%56,%57,%58,%59,%60,%61,%62,%63}, %64, %65, p, 1, 1, 1, 0;\n}\n"
    : "+f"(d[0]), "+f"(d[1]), "+f"(d[2]), "+f"(d[3]), "+f"(d[4]), "+f"(d[5]), "+f"(d[6]), "+f"(d[7]), "+f"(d[8]), "+f"(d[9]), "+f"(d[10]), "+f"(d[11]),
      "+f"(d[12]), "+f"(d[13]), "+f"(d[14]), "+f"(d[15]), "+f"(d[16]), "+f"(d[17]), "+f"(d[18]), "+f"(d[19]), "+f"(d[20]), "+f"(d[21]), "+f"(d[22]), "+f"(d[23]),
      "+f"(d[24]), "+f"(d[25]), "+f"(d[26]), "+f"(d[27]), "+f"(d[28]), "+f"(d[29]), "+f"(d[30]), "+f"(d[31]), "+f"(d[32]), "+f"(d[33]), "+f"(d[34]), "+f"(d[35]),
      "+f"(d[36]), "+f"(d[37]), "+f"(d[38]), "+f"(d[39]), "+f"(d[40]), "+f"(d[41]), "+f"(d[42]), "+f"(d[43]), "+f"(d[44]), "+f"(d[45]), "+f"(d[46]), "+f"(d[47]),
      "+f"(d[48]), "+f"(d[49]), "+f"(d[50]), "+f"(d[51]), "+f"(d[52]), "+f"(d[53]), "+f"(d[54]), "+f"(d[55]), "+f"(d[56]), "+f"(d[57]), "+f"(d[58]), "+f"(d[59]),
      "+f"(d[60]), "+f"(d[61]), "+f"(d[62]), "+f"(d[63])
    : "l"(da), "l"(db), "r"(acc));
}
__device__ __forceinline__ void wg_ss_n128_bt(float (&d)[64], uint64_t da, uint64_t db, int acc) {
  asm volatile("{\n.reg .pred p;\nsetp.ne.b32 p, %66, 0;\n"
      "wgmma.mma_async.sync.aligned.m64n128k16.f32.bf16.bf16 {%0,%1,%2,%3,%4,%5,%6,%7,%8,%9,%10,%11,%12,%13,%14,%15,%16,%17,%18,%19,%20,%21,%22,%23,"
      "%24,%25,%26,%27,%28,%29,%30,%31,%32,%33,%34,%35,%36,%37,%38,%39,%40,%41,%42,%43,%44,%45,%46,%47,"
      "%48,%49,%50,%51,%52,%53,%54,%55,%56,%57,%58,%59,%60,%61,%62,%63}, %64, %65, p, 1, 1, 0, 1;\n}\n"
    : "+f"(d[0]), "+f"(d[1]), "+f"(d[2]), "+f"(d[3]), "+f"(d[4]), "+f"(d[5]), "+f"(d[6]), "+f"(d[7]), "+f"(d[8]), "+f"(d[9]), "+f"(d[10]), "+f"(d[11]),
      "+f"(d[12]), "+f"(d[13]), "+f"(d[14]), "+f"(d[15]), "+f"(d[16]), "+f"(d[17]), "+f"(d[18]), "+f"(d[19]), "+f"(d[20]), "+f"(d[21]), "+f"(d[22]), "+f"(d[23]),
      "+f"(d[24]), "+f"(d[25]), "+f"(d[26]), "+f"(d[27]), "+f"(d[28]), "+f"(d[29]), "+f"(d[30]), "+f"(d[31]), "+f"(d[32]), "+f"(d[33]), "+f"(d[34]), "+f"(d[35]),
      "+f"(d[36]), "+f"(d[37]), "+f"(d[38]), "+f"(d[39]), "+f"(d[40]), "+f"(d[41]), "+f"(d[42]), "+f"(d[43]), "+f"(d[44]), "+f"(d[45]), "+f"(d[46]), "+f"(d[47]),
      "+f"(d[48]), "+f"(d[49]), "+f"(d[50]), "+f"(d[51]), "+f"(d[52]), "+f"(d[53]), "+f"(d[54]), "+f"(d[55]), "+f"(d[56]), "+f"(d[57]), "+f"(d[58]), "+f"(d[59]),
      "+f"(d[60]), "+f"(d[61]), "+f"(d[62]), "+f"(d[63])
    : "l"(da), "l"(db), "r"(acc));
}
__device__ __forceinline__ void wg_ss_n8_at(float (&d)[4], uint64_t da, uint64_t db, int acc) {
  asm volatile("{\n.reg .pred p;\nsetp.ne.b32 p, %6, 0;\n"
      "wgmma.mma_async.sync.aligned.m64n8k16.f32.bf16.bf16 {%0,%1,%2,%3}, %4, %5, p, 1, 1, 1, 0;\n}\n"
    : "+f"(d[0]), "+f"(d[1]), "+f"(d[2]), "+f"(d[3])
    : "l"(da), "l"(db), "r"(acc));
}
__device__ __forceinline__ void wg_ss_qk(float (&d)[32], uint64_t da, uint64_t db, int acc) {
  asm volatile("{\n.reg .pred p;\nsetp.ne.b32 p, %34, 0;\n"
      "wgmma.mma_async.sync.aligned.m64n64k16.f32.f16.f16 {%0,%1,%2,%3,%4,%5,%6,%7,%8,%9,%10,%11,%12,%13,%14,%15,%16,%17,%18,%19,%20,%21,%22,%23,"
      "%24,%25,%26,%27,%28,%29,%30,%31}, %32, %33, p, 1, 1, 0, 1;\n}\n"
    : "+f"(d[0]), "+f"(d[1]), "+f"(d[2]), "+f"(d[3]), "+f"(d[4]), "+f"(d[5]), "+f"(d[6]), "+f"(d[7]), "+f"(d[8]), "+f"(d[9]), "+f"(d[10]), "+f"(d[11]),
      "+f"(d[12]), "+f"(d[13]), "+f"(d[14]), "+f"(d[15]), "+f"(d[16]), "+f"(d[17]), "+f"(d[18]), "+f"(d[19]), "+f"(d[20]), "+f"(d[21]), "+f"(d[22]), "+f"(d[23]),
      "+f"(d[24]), "+f"(d[25]), "+f"(d[26]), "+f"(d[27]), "+f"(d[28]), "+f"(d[29]), "+f"(d[30]), "+f"(d[31])
    : "l"(da), "l"(db), "r"(acc));
}
__device__ __forceinline__ void wg_rs_pv(uint32_t (&d)[6], uint32_t a0, uint32_t a1, uint32_t a2, uint32_t a3, uint64_t db) {
  asm volatile("wgmma.mma_async.sync.aligned.m64n24k16.f16.f16.f16 {%0,%1,%2,%3,%4,%5}, {%6,%7,%8,%9}, %10, 1, 1, 1, 0;\n"
    : "+r"(d[0]), "+r"(d[1]), "+r"(d[2]), "+r"(d[3]), "+r"(d[4]), "+r"(d[5])
    : "r"(a0), "r"(a1), "r"(a2), "r"(a3), "l"(db));
}
__device__ __forceinline__ void wg_rs_pv0(uint32_t (&d)[6], uint32_t a0, uint32_t a1, uint32_t a2, uint32_t a3, uint64_t db) {
  asm volatile("wgmma.mma_async.sync.aligned.m64n24k16.f16.f16.f16 {%0,%1,%2,%3,%4,%5}, {%6,%7,%8,%9}, %10, 0, 1, 1, 0;\n"
    : "+r"(d[0]), "+r"(d[1]), "+r"(d[2]), "+r"(d[3]), "+r"(d[4]), "+r"(d[5])
    : "r"(a0), "r"(a1), "r"(a2), "r"(a3), "l"(db));
}

__device__ __forceinline__ void wg_fence() { asm volatile("wgmma.fence.sync.aligned;" ::: "memory"); }
__device__ __forceinline__ void wg_commit() { asm volatile("wgmma.commit_group.sync.aligned;" ::: "memory"); }
template <int N> __device__ __forceinline__ void wg_wait() { asm volatile("wgmma.wait_group.sync.aligned %0;" ::"n"(N) : "memory"); }
template <int N> __device__ __forceinline__ void reg_fence(float (&r)[N]) {
#pragma unroll
    for (int i = 0; i < N; i++) asm volatile("" : "+f"(r[i])::"memory");
}
template <int N> __device__ __forceinline__ void reg_fence(uint32_t (&r)[N]) {
#pragma unroll
    for (int i = 0; i < N; i++) asm volatile("" : "+r"(r[i])::"memory");
}
__device__ __forceinline__ void mbar_init(uint32_t bar, int cnt) { asm volatile("mbarrier.init.shared::cta.b64 [%0], %1;" ::"r"(bar), "r"(cnt) : "memory"); }
__device__ __forceinline__ void mbar_expect(uint32_t bar, int bytes) { asm volatile("mbarrier.arrive.expect_tx.shared::cta.b64 _, [%0], %1;" ::"r"(bar), "r"(bytes) : "memory"); }
__device__ __forceinline__ void mbar_arrive(uint32_t bar) { asm volatile("mbarrier.arrive.shared::cta.b64 _, [%0];" ::"r"(bar) : "memory"); }
__device__ __forceinline__ void mbar_wait(uint32_t bar, int parity) {
    asm volatile("{\n.reg .pred p;\n.reg .u32 n;\nmov.u32 n, 0;\n"
                 "W_%=:\nmbarrier.try_wait.parity.shared::cta.b64 p, [%0], %1;\n@p bra D_%=;\n"
                 "add.u32 n, n, 1;\nsetp.lt.u32 p, n, 0x4000000;\n@p bra W_%=;\ntrap;\nD_%=:\n}" ::"r"(bar), "r"(parity) : "memory");
}
__device__ __forceinline__ void mbar_wait_u(uint32_t bar, int parity) {
    for (uint32_t n = 0;; n++) {
        uint32_t ok;
        asm volatile("{\n.reg .pred p;\nmbarrier.try_wait.parity.shared::cta.b64 p, [%1], %2;\nselp.u32 %0, 1, 0, p;\n}" : "=r"(ok) : "r"(bar), "r"(parity) : "memory");
        if (__all_sync(~0u, ok)) break;
        if (n > 0x4000000u) __trap();
    }
}
__device__ __forceinline__ uint32_t mbar_probe(uint32_t bar, int parity) {
    uint32_t ok;
    asm volatile("{\n.reg .pred p;\nmbarrier.test_wait.parity.shared::cta.b64 p, [%1], %2;\nselp.u32 %0, 1, 0, p;\n}" : "=r"(ok) : "r"(bar), "r"(parity) : "memory");
    return ok;
}
__device__ __forceinline__ void mbar_finish(uint32_t ok, uint32_t bar, int parity) {
    asm volatile("{\n.reg .pred p;\n.reg .u32 n;\nsetp.ne.u32 p, %2, 0;\n@p bra.uni D_%=;\nmov.u32 n, 0;\n"
                 "W_%=:\nmbarrier.try_wait.parity.shared::cta.b64 p, [%0], %1;\n@p bra.uni D_%=;\n"
                 "add.u32 n, n, 1;\nsetp.lt.u32 p, n, 0x4000000;\n@p bra.uni W_%=;\ntrap;\nD_%=:\n}" ::"r"(bar), "r"(parity), "r"(ok) : "memory");
}
__device__ __forceinline__ void tma2d(uint32_t dst, const CUtensorMap* m, int c0, int c1, uint32_t bar) {
    asm volatile("cp.async.bulk.tensor.2d.shared::cluster.global.mbarrier::complete_tx::bytes [%0], [%1, {%2, %3}], [%4];"
                 ::"r"(dst), "l"(m), "r"(c0), "r"(c1), "r"(bar) : "memory");
}
__device__ __forceinline__ void tma3d(uint32_t dst, const CUtensorMap* m, int c0, int c1, int c2, uint32_t bar) {
    asm volatile("cp.async.bulk.tensor.3d.shared::cluster.global.mbarrier::complete_tx::bytes [%0], [%1, {%2, %3, %4}], [%5];"
                 ::"r"(dst), "l"(m), "r"(c0), "r"(c1), "r"(c2), "r"(bar) : "memory");
}
__device__ __forceinline__ void tma4d(uint32_t dst, const CUtensorMap* m, int c0, int c1, int c2, int c3, uint32_t bar) {
    asm volatile("cp.async.bulk.tensor.4d.shared::cluster.global.mbarrier::complete_tx::bytes [%0], [%1, {%2, %3, %4, %5}], [%6];"
                 ::"r"(dst), "l"(m), "r"(c0), "r"(c1), "r"(c2), "r"(c3), "r"(bar) : "memory");
}
__device__ __forceinline__ void l2_prefetch(const void* src, int bytes) {
    asm volatile("cp.async.bulk.prefetch.L2.global [%0], %1;" ::"l"(src), "r"(bytes) : "memory");
}
__device__ __forceinline__ void bulk_ld(uint32_t dst, const void* src, int bytes, uint32_t bar) {
    asm volatile("cp.async.bulk.shared::cluster.global.mbarrier::complete_tx::bytes [%0], [%1], %2, [%3];"
                 ::"r"(dst), "l"(src), "r"(bytes), "r"(bar) : "memory");
}
__device__ __forceinline__ void fence_async_s() { asm volatile("fence.proxy.async.shared::cta;" ::: "memory"); }
__device__ __forceinline__ void fence_async_g() { asm volatile("fence.proxy.async.global;" ::: "memory"); }
__device__ __forceinline__ void cnt_arrive(int i) {
    asm volatile("red.release.gpu.global.add.u32 [%0], 1;" ::"l"(&g_cnt[i * 32]) : "memory");
}
__device__ __forceinline__ void cnt_wait(int i, uint32_t target) {
    for (uint32_t n = 0;; n++) {
        uint32_t v;
        asm volatile("ld.acquire.gpu.global.u32 %0, [%1];" : "=r"(v) : "l"(&g_cnt[i * 32]) : "memory");
        if ((int)(v - target) >= 0) break;
        if (n > 0x800000u) __trap();
    }
}
__device__ __forceinline__ void named_sync(int id, int n) { asm volatile("bar.sync %0, %1;" ::"r"(id), "r"(n) : "memory"); }
__device__ __forceinline__ uint32_t pack_h2(float lo, float hi) { uint32_t r; asm("cvt.rn.f16x2.f32 %0, %1, %2;" : "=r"(r) : "f"(hi), "f"(lo)); return r; }
__device__ __forceinline__ uint32_t pack_b2(float lo, float hi) { uint32_t r; asm("cvt.rn.bf16x2.f32 %0, %1, %2;" : "=r"(r) : "f"(hi), "f"(lo)); return r; }
__device__ __forceinline__ float2 h2f(uint32_t v) {
    float2 r;
    asm("{.reg .b16 a, b; mov.b32 {a, b}, %2; cvt.f32.f16 %0, a; cvt.f32.f16 %1, b;}" : "=f"(r.x), "=f"(r.y) : "r"(v));
    return r;
}
__device__ __forceinline__ float blo(uint32_t v) { return __uint_as_float(v << 16); }
__device__ __forceinline__ float bhi(uint32_t v) { return __uint_as_float(v & 0xffff0000u); }
__device__ __forceinline__ float rbf(float v) { return __bfloat162float(__float2bfloat16_rn(v)); }
__device__ __forceinline__ float frcp(float v) { float r; asm("rcp.approx.ftz.f32 %0, %1;" : "=f"(r) : "f"(v)); return r; }
__device__ __forceinline__ float sigmoidf_(float v) { return frcp(1.f + __expf(-v)); }
__host__ __device__ constexpr uint64_t mkdesc(uint32_t off, uint32_t lbo, uint32_t sbo, uint32_t swz) {
    return (uint64_t)((SBASE + off) >> 4) | ((uint64_t)(lbo >> 4) << 16) | ((uint64_t)(sbo >> 4) << 32) | ((uint64_t)swz << 62);
}

template <int T> __device__ __forceinline__ uint32_t exp_pair(float a, float b, uint32_t c3c) {
    uint32_t r;
    if (T == 0) {
        float x, y;
        asm("ex2.approx.ftz.f32 %0, %1;" : "=f"(x) : "f"(a));
        asm("ex2.approx.ftz.f32 %0, %1;" : "=f"(y) : "f"(b));
        r = pack_h2(x, y);
    } else {
        uint32_t y;
        asm("prmt.b32 %0, %1, %2, 0x6521;" : "=r"(y) : "r"(__float_as_uint(a)), "r"(__float_as_uint(b)));
        if (T == 2) {
            uint32_t m, e = y | 0x03ff03ffu;
            asm("lop3.b32 %0, %1, 0x03ff03ff, %2, 0xea;" : "=r"(m) : "r"(y), "r"(c3c));
            asm("fma.rn.relu.f16x2 %0, %1, %2, %3;" : "=r"(r) : "r"(y), "r"(m), "r"(e));
        } else {
            uint32_t z = 0xfbdafbdau - y, w;
            asm("{.reg .b32 c; mov.b32 c, 0x45304530; fma.rn.f16x2 %0, %1, %2, c;}" : "=r"(w) : "r"(y), "r"(z));
            asm("fma.rn.relu.f16x2 %0, %1, %2, %1;" : "=r"(r) : "r"(y), "r"(w));
        }
    }
    return r;
}
template <int I> struct ExpLoop {
    static __device__ __forceinline__ void run(float (&s)[32], uint32_t (&p)[16], uint32_t c3c) {
        p[I] = exp_pair<pat_of(I)>(s[2 * I], s[2 * I + 1], c3c);
        ExpLoop<I + 1>::run(s, p, c3c);
    }
};
template <> struct ExpLoop<16> { static __device__ __forceinline__ void run(float (&)[32], uint32_t (&)[16], uint32_t) {} };
__device__ __forceinline__ void init_s(float (&s)[32], uint32_t a) {
#pragma unroll
    for (int j = 0; j < 8; j++)
        asm volatile("ld.shared.v4.f32 {%0, %1, %2, %3}, [%4];" : "=f"(s[4 * j]), "=f"(s[4 * j + 1]), "=f"(s[4 * j + 2]), "=f"(s[4 * j + 3])
                     : "r"(a + 16 * j));
}
__device__ __forceinline__ uint32_t hfma2(uint32_t a, uint32_t b, uint32_t c) { uint32_t r; asm("fma.rn.f16x2 %0, %1, %2, %3;" : "=r"(r) : "r"(a), "r"(b), "r"(c)); return r; }
__device__ __forceinline__ bool wg_any(int id, bool v) {
    uint32_t r;
    asm volatile("{\n.reg .pred p, q;\nsetp.ne.u32 q, %2, 0;\nbar.red.or.pred p, %1, 128, q;\nselp.u32 %0, 1, 0, p;\n}" : "=r"(r) : "r"(id), "r"((uint32_t)v) : "memory");
    return r;
}

__device__ __noinline__ void attn_slow(uint8_t* scr, const __nv_bfloat16* x, const __nv_bfloat16* w, int head, int rowtile, uint8_t* dst, int frag, float gate, int bar) {
    const int r = threadIdx.x & 63, hf = (threadIdx.x >> 6) & 1;
    float q[16], o[16], m = -INFINITY, l = 0.f;
#pragma unroll
    for (int d = 0; d < 16; d++) o[d] = 0.f;
    for (int c = -1; c < 32; c++) {
        const __nv_bfloat16* xr = x + ((c < 0 ? rowtile : c) * 64 + r) * D_;
        const __nv_bfloat16* wc = w + (c < 0 ? 0 : 512 + hf * 512) + head * 16;
        float a[16];
#pragma unroll
        for (int d = 0; d < 16; d++) a[d] = 0.f;
        for (int k2 = 0; k2 < 256; k2++) {
            const uint32_t xv = *(const uint32_t*)(xr + k2 * 2);
#pragma unroll
            for (int kk = 0; kk < 2; kk++) {
                const float xf = kk ? bhi(xv) : blo(xv);
                const uint4 w0 = *(const uint4*)(wc + (k2 * 2 + kk) * 1536), w1 = *(const uint4*)(wc + (k2 * 2 + kk) * 1536 + 8);
                const uint32_t ws[8] = {w0.x, w0.y, w0.z, w0.w, w1.x, w1.y, w1.z, w1.w};
#pragma unroll
                for (int d = 0; d < 8; d++) { a[2 * d] += xf * blo(ws[d]); a[2 * d + 1] += xf * bhi(ws[d]); }
            }
        }
        if (c < 0) {
#pragma unroll
            for (int d = 0; d < 16; d++) q[d] = rbf(a[d]);
            continue;
        }
        named_sync(bar, 128);
#pragma unroll
        for (int d = 0; d < 8; d++) ((uint32_t*)(scr + r * 64 + hf * 32))[d] = pack_b2(a[2 * d], a[2 * d + 1]);
        named_sync(bar, 128);
        for (int k = hf * 32; k < hf * 32 + 32; k++) {
            const uint32_t* kv = (const uint32_t*)(scr + k * 64);
            float s = 0.f;
#pragma unroll
            for (int d = 0; d < 8; d++) { s += q[2 * d] * blo(kv[d]); s += q[2 * d + 1] * bhi(kv[d]); }
            s = rbf(rbf(s) * 0.25f);
            const float mn = fmaxf(m, s), cr = __expf(m - mn), p = __expf(s - mn);
            l = l * cr + p;
            m = mn;
#pragma unroll
            for (int d = 0; d < 8; d++) { o[2 * d] = o[2 * d] * cr + p * blo(kv[8 + d]); o[2 * d + 1] = o[2 * d + 1] * cr + p * bhi(kv[8 + d]); }
        }
    }
    float* f = (float*)scr;
    named_sync(bar, 128);
    f[(hf * 64 + r) * 2] = m; f[(hf * 64 + r) * 2 + 1] = l;
    named_sync(bar, 128);
    const float m2 = f[((hf ^ 1) * 64 + r) * 2], l2 = f[((hf ^ 1) * 64 + r) * 2 + 1], mn = fmaxf(m, m2), cr = __expf(m - mn);
    const float sc = gate * cr * frcp(l * cr + l2 * __expf(m2 - mn));
    named_sync(bar, 128);
#pragma unroll
    for (int d = 0; d < 8; d++) f[(d * 2 + hf) * 64 + r] = (hf ? o[d] : o[8 + d]) * sc;
    named_sync(bar, 128);
    float e[8];
#pragma unroll
    for (int d = 0; d < 8; d++) e[d] = (hf ? o[8 + d] : o[d]) * sc + f[(d * 2 + (hf ^ 1)) * 64 + r];
#pragma unroll
    for (int t = 0; t < 4; t++)
        *(uint32_t*)(dst + (frag ? (r >> 4) * 512 + (r & 7) * 64 + t * 16 + hf * 8 + ((r >> 3) & 1) * 4 : (r >> 3) * 256 + hf * 128 + (r & 7) * 16 + t * 4)) =
            pack_b2(e[2 * t], e[2 * t + 1]);
    named_sync(bar, 128);
}

template <int V> struct IC { static constexpr int v = V; };
struct Params {
    const __nv_bfloat16 *x, *wqkv, *w_r, *gate_w, *wg, *wu, *wd, *wo;
    __nv_bfloat16* out;
};

__device__ __forceinline__ void mod_cta(uint8_t* smem, uint32_t sb, const Params& P, const CUtensorMap* mg, const CUtensorMap* mu,
                                        const CUtensorMap* md) {
    const int tid = threadIdx.x, lane = tid & 31, warp = tid >> 5, wg = tid >> 7, part = blockIdx.x - 128;
    const uint32_t bars = sb + OFF_MISC;
    constexpr int NBOX = 44;
    auto issue = [&](int i) {
        const int st = i % M_STAGES;
        const uint32_t bar = bars + 8 * (B_AF + st), dst = sb + st * M_STAGE_BYTES;
        if (i < 28) {
            const int j = i < 24 ? (i >> 3) * 2 + (i & 1) : 6, q = i < 24 ? (i >> 1) & 3 : i & 3;
            mbar_expect(bar, 32768);
            tma2d(dst, (q & 2) ? mu : mg, part * 448 + j * 64, (q & 1) * 256, bar);
        } else {
            mbar_expect(bar, 28672);
            tma2d(dst, md, (((i - 28) >> 2) * 2 + (i & 1)) * 64, part * 448 + ((i >> 1) & 1) * 224, bar);
        }
    };
    __syncthreads();
    if (tid == 512) {
        const uint32_t ep = g_epoch[blockIdx.x] + 1;
        for (int i = 0; i < M_STAGES; i++) issue(i);
        g_epoch[blockIdx.x] = ep;
        cnt_wait(C_R, 128 * ep);
    }
    for (int i = tid; i < 4096; i += NTHR) ((uint32_t*)(smem + OFF_XSEL))[i] = 0;
    __syncthreads();
    unsigned long long b1 = 0, b2 = 0;
    if (tid < 512) {
        const float4 rv = __ldcg((const float4*)(g_r + tid * 4));
        const float rr[4] = {rv.x, rv.y, rv.z, rv.w};
#pragma unroll
        for (int j = 0; j < 4; j++) {
            uint32_t u = __float_as_uint(rr[j]);
            u = (u & 0x80000000u) ? ~u : (u | 0x80000000u);
            const unsigned long long k = ((unsigned long long)u << 32) | (uint32_t)(~(tid * 4 + j));
            if (k > b1) { b2 = b1; b1 = k; } else if (k > b2) b2 = k;
        }
    }
    auto merge = [&](int o) {
        const unsigned long long c1 = __shfl_xor_sync(~0u, b1, o), c2 = __shfl_xor_sync(~0u, b2, o);
        const unsigned long long hi = b1 > c1 ? b1 : c1, lo = b1 > c1 ? c1 : b1, s2 = b2 > c2 ? b2 : c2;
        b1 = hi; b2 = lo > s2 ? lo : s2;
    };
    for (int o = 16; o; o >>= 1) merge(o);
    unsigned long long* red = (unsigned long long*)(smem + OFF_MISC + 512);
    if (lane == 0) { red[warp * 2] = b1; red[warp * 2 + 1] = b2; }
    __syncthreads();
    b1 = red[(lane & 15) * 2]; b2 = red[(lane & 15) * 2 + 1];
    for (int o = 8; o; o >>= 1) merge(o);
    const int i0 = (int)(~(uint32_t)b1), i1 = (int)(~(uint32_t)b2);
    if (tid < 128) {
        const int t = tid >> 6, kc = tid & 63;
        *(uint4*)(smem + OFF_XSEL + kc * 128 + t * 16) = *(const uint4*)(P.x + (t ? i1 : i0) * D_ + kc * 8);
    }
    if (part == 0 && tid == 0) {
        g_sel[0] = i0; g_sel[1] = i1;
        g_sel[2] = __float_as_int(rbf(sigmoidf_(__ldcg(g_r + i0))));
        g_sel[3] = __float_as_int(rbf(sigmoidf_(__ldcg(g_r + i1))));
    }
    fence_async_s();
    __syncthreads();
    if (tid == 512) {
        for (int i = M_STAGES; i < NBOX; i++) {
            mbar_wait(bars + 8 * (B_AE + i % M_STAGES), (i / M_STAGES - 1) & 1);
            issue(i);
        }
    } else if (wg < 2) {
        const int w4 = warp & 3, g = lane >> 2;
        auto box = [&](float (&acc)[4], int i, int nk, uint32_t boff, int first) {
            const int st = i % M_STAGES;
            mbar_wait(bars + 8 * (B_AF + st), (i / M_STAGES) & 1);
            const uint64_t da = mkdesc(0, 8192, 1024, 1) + st * (M_STAGE_BYTES >> 4), db = mkdesc(0, 128, 256, 0) + (boff >> 4);
            reg_fence(acc);
            wg_fence();
            for (int k = 0; k < nk; k++) wg_ss_n8_at(acc, da + k * 128, db + k * 16, !(first && k == 0));
            wg_commit();
            wg_wait<0>();
            reg_fence(acc);
            named_sync(3 + wg, 128);
            if ((tid & 127) == 0) mbar_arrive(bars + 8 * (B_AE + st));
        };
#pragma unroll 1
        for (int j = wg; j < 7; j += 2) {
            float ag[4] = {0, 0, 0, 0}, au[4] = {0, 0, 0, 0};
            const int i = (j >> 1) * 8 + wg, di = j < 6 ? 2 : 1;
            box(ag, i, 16, OFF_XSEL, 1); box(ag, i + di, 16, OFF_XSEL + 4096, 0);
            box(au, i + 2 * di, 16, OFF_XSEL, 1); box(au, i + 3 * di, 16, OFF_XSEL + 4096, 0);
            if ((lane & 3) == 0) {
#pragma unroll
                for (int e = 0; e < 4; e++) {
                    const float gv = rbf(ag[e]), h = rbf(gv * sigmoidf_(gv)) * rbf(au[e]);
                    const int f = j * 64 + w4 * 16 + (e >> 1) * 8 + g;
                    *(__nv_bfloat16*)(smem + OFF_HSEL + (f >> 3) * 128 + (e & 1) * 16 + (f & 7) * 2) = __float2bfloat16_rn(h);
                }
            }
        }
        fence_async_s();
        named_sync(1, 256);
#pragma unroll 1
        for (int j = wg; j < 8; j += 2) {
            float a[4] = {0, 0, 0, 0};
            const int i = 28 + (j >> 1) * 4 + wg;
            box(a, i, 14, OFF_HSEL, 1); box(a, i + 2, 14, OFF_HSEL + 14 * 256, 0);
            if ((lane & 3) == 0) {
#pragma unroll
                for (int e = 0; e < 4; e++) g_y[(part * 2 + (e & 1)) * D_ + j * 64 + w4 * 16 + (e >> 1) * 8 + g] = a[e];
            }
        }
        named_sync(1, 256);
        if (tid == 0) { cnt_arrive(C_Y); TSTAMP(1); }
    }
}

__global__ void __launch_bounds__(NTHR, 1)
fused_kernel(const __grid_constant__ CUtensorMap mx, const __grid_constant__ CUtensorMap mkv, const __grid_constant__ CUtensorMap mq,
             const __grid_constant__ CUtensorMap mo, const __grid_constant__ CUtensorMap mg,
             const __grid_constant__ CUtensorMap mu, const __grid_constant__ CUtensorMap md, const __grid_constant__ Params P) {
    extern __shared__ __align__(1024) uint8_t smem[];
    constexpr uint32_t sb = SBASE, bars = sb + OFF_MISC;
    const int tid = threadIdx.x, lane = tid & 31, warp = __shfl_sync(~0u, tid >> 5, 0), wg = warp >> 2, w4 = warp & 3;
    const int cta = blockIdx.x;
    volatile uint32_t* misc = (volatile uint32_t*)(smem + OFF_MISC + 320);
    volatile float* gate = (volatile float*)(smem + OFF_MISC + 512);
    const int nt = NTX, mt = MTX;
    const int rt = 2 * mt + (nt & 1), ct = nt >> 1;

    if (lane == 0) {
        if (warp == 16) {
            TSTAMP(0);
#pragma unroll
            for (int i = 0; i < 8; i++) mbar_init(bars + 8 * (B_AF + i), 1);
            fence_async_s();
            if (cta < 128) {
#pragma unroll
                for (int kc = 0; kc < 8; kc++) {
                    const uint32_t bar = bars + 8 * (B_AF + kc);
                    mbar_expect(bar, 32768);
                    tma2d(sb + off_x(kc), &mx, kc * 64, mt * 128, bar);
                    if (kc < 6) tma3d(sb + off_w(kc), &mkv, nt * 64, kc * 64, 1, bar);
                }
                TSTAMP(15);
            }
        } else if (wg < 4) {
            const uint32_t c = cta < 128 ? (uint32_t)(BAR_CNT >> (warp * 4)) & 15 : 0;
            mbar_init(bars + 8 * (8 + 2 * warp), c + 1);
            mbar_init(bars + 8 * (9 + 2 * warp), c + 1);
            fence_async_s();
            misc[1] = 0; misc[2] = 0;
            if ((uint32_t)__cvta_generic_to_shared(smem) != SBASE) __trap();
        }
    }
    __syncwarp();
    if (cta >= 128) {
        mod_cta(smem, sb, P, &mg, &mu, &md);
        return;
    }

    if (wg == 4) {
        const uint32_t ep = g_epoch[cta] + 1;
        named_sync(7, NTHR);
        if (warp == 17) {
        if (lane == 0) {
            mbar_wait(bars + 8 * B_KVP, 0);
            TSTAMP(7);
            cnt_arrive(C_KV + nt);
            cnt_wait(C_R, 128 * ep);
            cnt_wait(C_KV + nt, 16 * ep);
            mbar_wait(bars + 8 * B_AFREE, 0);
        }
        __syncwarp();
        ((float4*)gate)[lane] = __ldcg((const float4*)(g_g + mt * 128) + lane);
        {
            const uint4 v = __ldcg((const uint4*)(g_mx + nt * 128) + lane);
            uint32_t m = max(max(v.x, v.y), max(v.z, v.w));
            m = max(m, __shfl_xor_sync(~0u, m, 1));
            m = max(m, __shfl_xor_sync(~0u, m, 2));
            const float k2 = __uint_as_float(__shfl_sync(~0u, m, (lane & 3) * 4)), vm = __uint_as_float(__shfl_sync(~0u, m, 16 + (lane & 3) * 4));
            const float q2 = __uint_as_float(misc[8 + (lane & 3)]);
            if (lane < 4) misc[4 + lane] = q2 * k2 <= BOUND_MAX * BOUND_MAX && q2 <= 65536.f && k2 <= 65536.f && vm >= 0.03125f ? 0x43800000u : 0x7f800000u;
        }
        __syncwarp();
        if (lane == 0) {
            mbar_arrive(bars + 8 * B_CHK);
            l2_prefetch(P.wg + cta * 7168, 14336); l2_prefetch(P.wu + cta * 7168, 14336); l2_prefetch(P.wd + cta * 7168, 14336);
            l2_prefetch(P.wo + cta * 2048, 4096);
            mbar_wait(bars + 8 * (B_KF + 3), 0);
            mbar_expect(bars + 8 * B_WOE, 65536);
            for (int j = 0; j < 2; j++) tma4d(sb + OFF_WOE + j * 32768, &mo, ct * 128 + j * 64, 0, 0, 0, bars + 8 * B_WOE);
        }
        __syncwarp();
        }
        if (warp == 16) {
        auto kv_stage = [&](int s) {
            const uint32_t bar = bars + 8 * (B_KF + (s & 3)), dst = sb + (s & 3) * SLOT;
            const uint8_t* src = g_kv + (nt * 16 + s) * 32768;
            mbar_expect(bar, 32768);
            bulk_ld(dst, src, 16384, bar);
            bulk_ld(dst + 18432, src + 16384, 16384, bar);
        };
        if (lane == 0) {
            g_epoch[cta] = ep;
#pragma unroll 1
            for (int i = 0; i < 6; i++) {
                mbar_wait(bars + 8 * (B_AE + i), 0);
                if (i < 2) tma3d(sb + off_w(i), &mkv, nt * 64, (6 + i) * 64, 1, bars + 8 * (B_AF + 6 + i));
                else {
                    mbar_expect(bars + 8 * (B_QF + i - 2), 16384);
                    tma2d(sb + off_w(i), &mq, nt * 64, (i - 2) * 128, bars + 8 * (B_QF + i - 2));
                }
            }
            mbar_wait(bars + 8 * B_GO, 0);
            TSTAMP(12);
            if (mt < 8) cnt_arrive(C_U + nt);
            mbar_arrive(bars + 8 * B_HOLD);
            TSTAMP(3);
            cnt_wait(C_U + nt, 8 * ep);
            TSTAMP(4);
            fence_async_g();
            {
                const uint8_t* src = g_kv + nt * 16 * 32768;
                mbar_expect(bars + 8 * B_K0, 4096);
                bulk_ld(sb, src, 2048, bars + 8 * B_K0);
                bulk_ld(sb + 24576, src + 22528, 2048, bars + 8 * B_K0);
                mbar_expect(bars + 8 * B_KF, 28672);
                bulk_ld(sb + 2048, src + 2048, 14336, bars + 8 * B_KF);
                bulk_ld(sb + 18432, src + 16384, 6144, bars + 8 * B_KF);
                bulk_ld(sb + 26624, src + 24576, 8192, bars + 8 * B_KF);
            }
            mbar_wait(bars + 8 * B_AFREE, 0);
            for (int s = 1; s <= GOJ / 4; s++) kv_stage(s);
            cnt_wait(C_KV + nt, 16 * ep);
            fence_async_g();
            for (int s = GOJ / 4 + 1; s < 4; s++) kv_stage(s);
            TSTAMP(19);
#pragma unroll 1
            for (int s = 4; s < 16; s++) {
                mbar_wait(bars + 8 * (B_KF + ((s - 2) & 3)), ((s - 2) >> 2) & 1);
                if (s == 8) mbar_wait(bars + 8 * B_CHK, 0);
                kv_stage(s);
            }
            TSTAMP(18);
            mbar_arrive(bars + 8 * B_KF);
            mbar_wait(bars + 8 * B_OP, 0);
            cnt_arrive(C_O + mt);
            cnt_wait(C_Y, 4 * ep);
        }
        __syncwarp();
        }
        named_sync(9, 128);
        float acc[64];
        {
            const int4 sel = __ldcg((const int4*)g_sel);
            uint32_t* bsel = (uint32_t*)(smem + OFF_BSEL);
            if ((sel.x >> 6) == rt || (sel.y >> 6) == rt) {
                const int t = w4 >> 1, c = ct * 128 + (tid & 63) * 2;
                const float rs = __int_as_float(t ? sel.w : sel.z);
                const uint32_t xv = *(const uint32_t*)(P.x + (t ? sel.y : sel.x) * D_ + c);
                float y0 = 0.f, y1 = 0.f;
#pragma unroll
                for (int pp = 0; pp < 4; pp++) {
                    const float2 v = __ldcg((const float2*)(g_y + (pp * 2 + t) * D_ + c));
                    y0 += v.x; y1 += v.y;
                }
                bsel[tid - 512] = pack_b2(blo(xv) + rbf(rbf(y0) * rs), bhi(xv) + rbf(rbf(y1) * rs));
                named_sync(9, 128);
            }
#pragma unroll
            for (int h = 0; h < 2; h++) {
                const int lr = (nt & 1) * 64 + w4 * 16 + (lane >> 2) + 8 * h, r = mt * 128 + lr;
                const float g = 1.f - gate[lr];
                const uint32_t* xp = (r == sel.x ? bsel : r == sel.y ? bsel + 64 : (const uint32_t*)(P.x + r * D_ + ct * 128)) + (lane & 3);
#pragma unroll
                for (int j = 0; j < 16; j++) { const uint32_t xv = xp[j * 4]; acc[4 * j + 2 * h] = g * blo(xv); acc[4 * j + 2 * h + 1] = g * bhi(xv); }
            }
        }
        __syncwarp();
        if (tid == 512) {
            TSTAMP(17);
            mbar_wait(bars + 8 * (B_KF + 2), 1);
            cnt_wait(C_O + mt, 8 * ep);
            fence_async_g();
            mbar_expect(bars + 8 * B_OE, 32768);
            bulk_ld(sb, g_o + rt * 65536, 32768, bars + 8 * B_OE);
            mbar_expect(bars + 8 * B_WL, 65536);
            for (int j = 0; j < 2; j++) {
                mbar_wait(bars + 8 * (B_KF + 3 - 3 * j), 1 - j);
                tma4d(sb + (1 + j) * SLOT, &mo, ct * 128 + j * 64, 0, 1, 0, bars + 8 * B_WL);
            }
            mbar_wait(bars + 8 * B_TRG, 0);
            TSTAMP(16);
        }
        __syncwarp();
        named_sync(9, 128);
        mbar_wait_u(bars + 8 * B_WOE, 0);
        mbar_wait_u(bars + 8 * B_OE, 0);
        reg_fence(acc);
        wg_fence();
#pragma unroll
        for (int k = 0; k < 16; k++) wg_ss_n128_bt(acc, mkdesc(k * 2048, 128, 256, 0), mkdesc(OFF_WOE + k * 2048, 32768, 1024, 1), 1);
        wg_commit();
        mbar_wait_u(bars + 8 * B_WL, 0);
        if (tid == 512) TSTAMP(8);
#pragma unroll
        for (int t = 0; t < 4; t++) {
            mbar_wait_u(bars + 8 * (B_OL + t), 0);
            if (tid == 512 && t == 1) TSTAMP(13);
            if (tid == 512 && t == 3) TSTAMP(9);
            const uint32_t c = __shfl_sync(~0u, misc[40 + t], 0);
            const uint64_t da = mkdesc(0, 128, 256, 0) + (c & 0xffff), db = mkdesc(SLOT, SLOT, 1024, 1) + (c >> 16);
            wg_fence();
#pragma unroll
            for (int i = 0; i < 4; i++) wg_ss_n128_bt(acc, da + i * 128, db + i * 512, 1);
            wg_commit();
        }
        wg_wait<0>();
        reg_fence(acc);
        if (tid == 512) TSTAMP(10);
        const uint32_t stg = sb + 3 * SLOT + 18432 + w4 * 4096, sa = stg + (lane & 15) * 128;
#pragma unroll
        for (int j = 0; j < 16; j += 2) {
            uint32_t v[4];
#pragma unroll
            for (int e = 0; e < 4; e++) v[e] = pack_b2(acc[4 * j + 2 * e], acc[4 * j + 2 * e + 1]);
            asm volatile("stmatrix.sync.aligned.m8n8.x4.shared.b16 [%0], {%1, %2, %3, %4};"
                         ::"r"(sa + (j >> 3) * 2048 + ((((j & 7) + (lane >> 4)) ^ (lane & 7)) << 4)), "r"(v[0]), "r"(v[1]), "r"(v[2]), "r"(v[3]) : "memory");
        }
        __syncwarp();
        uint4* od = (uint4*)(P.out + (rt * 64 + w4 * 16 + (lane >> 4)) * D_ + ct * 128) + (lane & 15);
#pragma unroll
        for (int i = 0; i < 8; i++) {
            const int r = 2 * i + (lane >> 4);
            uint4 v;
            asm volatile("ld.shared.v4.u32 {%0, %1, %2, %3}, [%4];" : "=r"(v.x), "=r"(v.y), "=r"(v.z), "=r"(v.w)
                         : "r"(stg + (lane & 8) * 256 + r * 128 + (((lane & 7) ^ (r & 7)) << 4)) : "memory");
            od[i * 128] = v;
        }
        if (tid == 512) TSTAMP(11);
        return;
    }

    if (wg < 2) {
        if (wg == 0) {
            *(uint4*)(smem + 16384 + tid * 16) = make_uint4(0x3c003c00u, 0x3c003c00u, 0x3c003c00u, 0x3c003c00u);
            fence_async_s();
        }
        const int st = w4 & 1, cg = mt & 7;
        uint8_t* const dst = g_kv + ((nt * 2 + (w4 >> 1)) * 8 + (mt >> 3) * 4) * 32768 + st * 16384 + lane * 4 + (wg ? cg * 128 : st * 6144 + cg * 256);
        const int o00 = st ? 0 : 12288;
        auto kslot = [&](int j, int h) { return (uint32_t*)(dst + (j >> 2) * 32768 + ((j >> 1) & 1) * 6144 + (j & 1) * 2048 + h * 128); };
        auto vslot = [&](int j, int h) { return (uint32_t*)(dst + (j >> 2) * 32768 + ((j & 2) ? 4096 + h * 6144 : o00 + h * 2048) + (j & 1) * 1024); };
        named_sync(7, NTHR);
        float acc[64];
#pragma unroll
        for (int kc = 0; kc < 8; kc++) {
            mbar_wait_u(bars + 8 * (B_AF + kc), 0);
            if (kc == 0 && tid == 0) TSTAMP(1);
            const uint64_t da = mkdesc(off_w(kc % 6), 8192, 1024, 1) + wg * 512, db = mkdesc(off_x(kc), 16, 1024, 1);
            wg_fence();
#pragma unroll
            for (int kk = 0; kk < 4; kk++) wg_ss_n128_at(acc, da + kk * 128, db + kk * 2, kc + kk > 0);
            wg_commit();
            if (kc >= 1 && kc <= 6) {
                wg_wait<1>();
                if ((tid & 127) == 0) mbar_arrive(bars + 8 * (B_AE + kc - 1));
            }
        }
        wg_wait<0>();
        reg_fence(acc);
        if (tid == 0) TSTAMP(2);
        uint32_t mxv;
        const bool urgent = mt < 8 && w4 < 2;
        auto put = [&](auto j0, auto j1) {
            if (wg == 0) {
#pragma unroll
                for (int i = 4 * decltype(j0)::v; i < 4 * decltype(j1)::v; i += 2)
                    *kslot(i >> 2, i >> 1 & 1) = i >= 4 ? pack_h2(acc[i] - acc[i - 4], acc[i + 1] - acc[i - 3]) : pack_h2(acc[i], acc[i + 1]);
            } else {
#pragma unroll
                for (int i = 4 * decltype(j0)::v; i < 4 * decltype(j1)::v; i += 2) *vslot(i >> 2, i >> 1 & 1) = pack_h2(acc[i], acc[i + 1]);
            }
        };
        if (!QA) asm volatile("bar.arrive 8, 512;" ::: "memory");
        if (urgent) put(IC<0>(), IC<GOJ + 1>());
        if (QA) asm volatile("bar.arrive 8, 512;" ::: "memory");
        __syncwarp();
        if (lane == 0) mbar_arrive(bars + 8 * B_GO);
        if (mt < 8) mbar_wait_u(bars + 8 * B_HOLD, 0);
        if (!urgent) put(IC<0>(), IC<GOJ + 1>());
        put(IC<GOJ + 1>(), IC<16>());
        if (wg == 0) {
            uint32_t n[16];
#pragma unroll
            for (int j = 0; j < 16; j++) n[j] = pack_b2(acc[4 * j] * acc[4 * j] + acc[4 * j + 2] * acc[4 * j + 2], acc[4 * j + 1] * acc[4 * j + 1] + acc[4 * j + 3] * acc[4 * j + 3]);
            auto fold = [&](auto oc) {
                constexpr int o = decltype(oc)::v;
                const bool up = lane & (2 * o);
#pragma unroll
                for (int i = 0; i < o; i++) {
                    const uint32_t t = __shfl_xor_sync(~0u, up ? n[i] : n[i + o], 2 * o), k = up ? n[i + o] : n[i];
                    asm("add.bf16x2 %0, %1, %2;" : "=r"(n[i]) : "r"(t), "r"(k));
                }
            };
            fold(IC<8>()); fold(IC<4>()); fold(IC<2>());
            mxv = max(max(n[0] << 16, n[0] & 0xffff0000u), max(n[1] << 16, n[1] & 0xffff0000u));
        } else {
            float mm = 0.f;
#pragma unroll
            for (int i = 0; i < 64; i++) mm = fmaxf(mm, fabsf(acc[i]));
            mxv = __float_as_uint(mm);
        }
        mxv = __reduce_max_sync(~0u, mxv);
        if (lane == 0) { g_mx[nt * 128 + warp * 16 + mt] = __uint_as_float(mxv); mbar_arrive(bars + 8 * B_KVP); }
        named_sync(1, 512);
    } else {
        {
            const int row0 = cta * 16 + (warp - 8) * 2;
            uint4 xv[2][2], wr[2], wgt[2];
#pragma unroll
            for (int c = 0; c < 2; c++) {
#pragma unroll
                for (int r = 0; r < 2; r++) xv[r][c] = *(const uint4*)(P.x + (row0 + r) * D_ + c * 256 + lane * 8);
                wr[c] = *(const uint4*)(P.w_r + c * 256 + lane * 8);
                wgt[c] = *(const uint4*)(P.gate_w + c * 256 + lane * 8);
            }
            named_sync(7, NTHR);
                auto dot8 = [](uint4 a, uint4 b) {
                return blo(a.x) * blo(b.x) + bhi(a.x) * bhi(b.x) + blo(a.y) * blo(b.y) + bhi(a.y) * bhi(b.y) +
                       blo(a.z) * blo(b.z) + bhi(a.z) * bhi(b.z) + blo(a.w) * blo(b.w) + bhi(a.w) * bhi(b.w);
            };
#pragma unroll
            for (int r = 0; r < 2; r++) {
                float a = dot8(xv[r][0], wr[0]) + dot8(xv[r][1], wr[1]), b = dot8(xv[r][0], wgt[0]) + dot8(xv[r][1], wgt[1]);
#pragma unroll
                for (int o = 16; o; o >>= 1) { a += __shfl_xor_sync(~0u, a, o); b += __shfl_xor_sync(~0u, b, o); }
                if (lane == 0) { g_r[row0 + r] = rbf(a); g_g[row0 + r] = sigmoidf_(b); }
            }
#pragma unroll
            for (int i = 0; i < 2; i++)
                *((uint4*)(g_o + (2 * mt + i) * 65536 + 32768 + nt * 4096) + (tid - 256)) = make_uint4(~0u, ~0u, ~0u, ~0u);
            named_sync(2, 256);
            if (tid == 256) cnt_arrive(C_R);
            __syncwarp();
        }
        uint32_t n[16];
        named_sync(8, 512);
        if (wg == 2) {
            float acc[64];
#pragma unroll
            for (int kc = 0; kc < 8; kc++) {
                if (!(kc & 1)) mbar_wait_u(bars + 8 * (B_QF + (kc >> 1)), 0);
                mbar_wait_u(bars + 8 * (B_AF + kc), 0);
                const uint64_t da = mkdesc(off_w(2 + (kc >> 1)) + (kc & 1) * 8192, 8192, 1024, 1), db = mkdesc(off_x(kc), 16, 1024, 1);
                wg_fence();
#pragma unroll
                for (int kk = 0; kk < 4; kk++) wg_ss_n128_at(acc, da + kk * 128, db + kk * 2, kc + kk > 0);
                wg_commit();
            }
            wg_wait<0>();
            reg_fence(acc);
            if (tid == 256) TSTAMP(14);
            named_sync(5, 128);
#pragma unroll
            for (int j = 0; j < 16; j += 2) {
                uint32_t v[4];
#pragma unroll
                for (int e = 0; e < 4; e++) v[e] = pack_h2(acc[4 * j + 2 * e] * QSCALE, acc[4 * j + 2 * e + 1] * QSCALE);
                asm volatile("stmatrix.sync.aligned.m8n8.x4.trans.shared.b16 [%0], {%1, %2, %3, %4};"
                             ::"r"(sb + off_q(w4 >> 1, (w4 & 1) * 2 + (j >> 3)) + (j & 7) * 256 + lane * 16), "r"(v[0]), "r"(v[1]), "r"(v[2]), "r"(v[3]) : "memory");
                n[j] = hfma2(v[0], v[0], hfma2(v[1], v[1], 0));
                n[j + 1] = hfma2(v[2], v[2], hfma2(v[3], v[3], 0));
            }
            if (w4 == 0) *(float*)(smem + OFF_INIT + lane * 4) = (PAT >> (lane >> 1) * 4 & 15) == 0 ? init_of_t(0) : (PAT >> (lane >> 1) * 4 & 15) == 2 ? init_of_t(2) : init_of_t(3);
            fence_async_s();
        }
        named_sync(1, 512);
        if (wg == 2) {
            auto fold = [&](auto oc) {
                constexpr int o = decltype(oc)::v;
                const bool up = lane & (2 * o);
#pragma unroll
                for (int i = 0; i < o; i++) {
                    const uint32_t t = __shfl_xor_sync(~0u, up ? n[i] : n[i + o], 2 * o), k = up ? n[i + o] : n[i];
                    asm("add.f16x2 %0, %1, %2;" : "=r"(n[i]) : "r"(t), "r"(k));
                }
            };
            fold(IC<8>()); fold(IC<4>()); fold(IC<2>());
            const uint32_t m = __reduce_max_sync(~0u, max(max(n[0] & 0xffff, n[0] >> 16), max(n[1] & 0xffff, n[1] >> 16)));
            if (lane == 0) misc[8 + w4] = __float_as_uint(h2f(m).x);
        } else {
#pragma unroll
            for (int i = 1; i < 4; i++) *(uint4*)(smem + i * SLOT + 16384 + (tid - 384) * 16) = make_uint4(0x3c003c00u, 0x3c003c00u, 0x3c003c00u, 0x3c003c00u);
        }
        fence_async_s();
        __syncwarp();
        if (lane == 0) mbar_arrive(bars + 8 * B_AFREE);
    }

    const int st = wg >> 1;
    uint8_t* const odst = g_o + (2 * mt + (wg & 1)) * 65536 + (nt * 2 + st) * 2048;
    uint32_t fail = 0;
    uint4 f[4];
    {
        float s[32];
        uint32_t o[6], o4 = 0, o5 = 0;
        uint64_t dq = mkdesc(0, 128, 256, 0) + (off_q(0, wg) >> 4);
        uint32_t c3c = 0x3c003c00u;
        asm volatile("" : "+r"(c3c));
        const uint64_t dk0 = mkdesc(0, 128, 256, 0) + st * (24576 >> 4);
        const uint64_t dv0 = mkdesc(12288, 128, 2048, 0) + st * (4096 >> 4), dw0 = mkdesc(4096, 128, 6144, 0) + st * (12288 >> 4);
        const bool sig = (tid & 127) == 0;
        uint32_t par = 0;
        auto rtid = []() { uint32_t t; asm volatile("mov.u32 %0, %%tid.x;" : "=r"(t)); return t & 127; };
        const uint32_t park = sb + off_q(1, wg) + (st ? 2048 : 4096);
        const uint32_t ia = sb + OFF_INIT + misc[1];
        init_s(s, ia);
        if (sig) mbar_arrive(bars + 8 * B_KF);
        mbar_wait_u(bars + 8 * B_K0, 0);
        if (tid == 0) { TSTAMP(5); CSTAMP(30); }
        wg_fence();
        wg_ss_qk(s, dq, dk0, 1);
        wg_commit();
        wg_wait<0>();
        reg_fence(s);
#define ATT_BLOCK(I, U, DN)                                                                                       \
    {                                                                                                             \
        uint32_t p[16], ok;                                                                                       \
        if (U == 3) { if (I == 3) par ^= 1; ok = mbar_probe(nb, par); }                                           \
        if (I + U == 0) ok = mbar_probe(bars + 8 * B_KF, par);                                                    \
        ExpLoop<0>::run(s, p, c3c);                                                                               \
        if (I == 3 && U == 3) {                     \
            init_s(s, ia);                                                                                        \
            if (seg & 1) dq = mkdesc(0, 128, 256, 0) + (off_q(1, wg) >> 4);                                       \
        }                                                                                                         \
        if (I + U == 0) mbar_finish(ok, bars + 8 * B_KF, par);                                                    \
        if (U == 3) mbar_finish(ok, nb, par);                                                                     \
        wg_fence();                                                                                               \
        wg_ss_qk(s, dq, DN, 1);                                                                                   \
        const uint64_t dp = (U < 2 ? dv : dw) + (U & 1) * 64;                                                     \
        if (NPV == 0) wg_commit();                                                                                \
        if (U == 0 && I == 0) wg_rs_pv0(o, p[0], p[1], p[2], p[3], dp);                                           \
        else wg_rs_pv(o, p[0], p[1], p[2], p[3], dp);                                                             \
        if (NPV == 1) wg_commit();                                                                                \
        wg_rs_pv(o, p[4], p[5], p[6], p[7], dp + 16);                                                             \
        if (NPV == 2) wg_commit();                                                                                \
        wg_rs_pv(o, p[8], p[9], p[10], p[11], dp + 32);                                                           \
        if (NPV == 3) wg_commit();                                                                                \
        wg_rs_pv(o, p[12], p[13], p[14], p[15], dp + 48);                                                         \
        wg_commit();                                                                                              \
        wg_wait<(I == 3 && U == 3) ? 0 : 1>();                                                                    \
        if (U == ARR && sig) mbar_arrive(nb);                                                                     \
        reg_fence(s);                                                                                             \
    }
#define ATT_STAGE(I)                                                                                              \
    {                                                                                                             \
        const uint64_t dk = dk0 + I * (SLOT >> 4), dv = dv0 + I * (SLOT >> 4), dw = dw0 + I * (SLOT >> 4);        \
        constexpr uint32_t nb = bars + 8 * (B_KF + ((I + 1) & 3));                                                \
        ATT_BLOCK(I, 0, dk + 128)                                                                                 \
        ATT_BLOCK(I, 1, dk + 384)                                                                                 \
        ATT_BLOCK(I, 2, dk + 512)                                                                                 \
        ATT_BLOCK(I, 3, dk0 + ((I + 1) & 3) * (SLOT >> 4))                                                        \
    }
#pragma unroll 1
        for (int seg = 0;; seg++) {
            ATT_STAGE(0) ATT_STAGE(1) ATT_STAGE(2) ATT_STAGE(3)
            reg_fence(o);
            const uint32_t t = rtid();
            if (!(seg & 1)) {
                asm volatile("st.shared.v4.u32 [%0], {%1, %2, %3, %4};" ::"r"(park + t * 16), "r"(o[0]), "r"(o[1]), "r"(o[2]), "r"(o[3]) : "memory");
                o4 = o[4]; o5 = o[5];
            } else {
                uint32_t o2[6];
                asm volatile("ld.shared.v4.u32 {%0, %1, %2, %3}, [%4];" : "=r"(o2[0]), "=r"(o2[1]), "=r"(o2[2]), "=r"(o2[3]) : "r"(park + t * 16) : "memory");
                o2[4] = o4; o2[5] = o5;
#pragma unroll
                for (int i = 0; i < 6; i++) asm("add.f16x2 %0, %0, %1;" : "+r"(o2[i]) : "r"(o[i]));
                const uint32_t ga = sb + OFF_MISC + 512 + (wg & 1) * 256 + (t >> 5) * 64 + (t & 28);
                float g0, g1, lmin;
                asm volatile("ld.shared.f32 %0, [%3];\nld.shared.f32 %1, [%3 + 32];\nld.shared.f32 %2, [%4];"
                             : "=f"(g0), "=f"(g1), "=f"(lmin) : "r"(ga), "r"(sb + OFF_MISC + 336 + 4 * (seg - 1 + st)));
                uint32_t w[4];
                bool ok;
                auto fin = [&](auto oc) {
                    constexpr int a = decltype(oc)::v;
                    const float l0 = h2f(o2[4 - 2 * a]).x, l1 = h2f(o2[5 - 2 * a]).x;
                    g0 *= frcp(l0); g1 *= frcp(l1);
#pragma unroll
                    for (int i = 0; i < 4; i++) {
                        const float2 v = h2f(o2[a + i]);
                        w[i] = pack_b2(v.x * ((i & 1) ? g1 : g0), v.y * ((i & 1) ? g1 : g0));
                    }
                    ok = l0 >= lmin && l1 >= lmin;
                };
                if (st) fin(IC<2>()); else fin(IC<0>());
                uint32_t z = 0;
#pragma unroll
                for (int i = 0; i < 6; i++) z = hfma2(o2[i], 0, z);
                ok = __all_sync(~0u, ok && z == 0);
                if (seg == 3) {
                    f[0] = make_uint4(w[0], w[1], w[2], w[3]);
                    if (ok) *(uint4*)(odst + 32768 + t * 16) = f[0];
                    else fail |= 2;
                    break;
                }
                if (!ok) fail |= 1;
                else {
#pragma unroll
                    for (int i = 0; i < 4; i++) ((uint32_t*)odst)[(t >> 5) * 128 + (t & 31) + (i >> 1) * 32 + (i & 1) * 64] = w[i];
                    __syncwarp();
                    if ((t & 31) == 0) mbar_arrive(bars + 8 * B_OP);
                }
            }
        }
        if (tid == 0) { TSTAMP(6); CSTAMP(31); }
    }
    if (lane == 0 && atomicAdd((uint32_t*)misc + 2, 1) == TRGN) mbar_arrive(bars + 8 * B_TRG);
    const bool slow = wg_any(3 + wg, fail);
    if (slow) {
        if (st == 0) named_sync(10, 256);
        for (int ps = 0; ps < 2; ps++)
            if (wg_any(3 + wg, (fail >> ps) & 1)) {
                attn_slow(smem + OFF_STG + (st ? (wg & 1) * 8192 : 16384 + wg * 4096), P.x, P.wqkv, nt * 4 + 2 * ps + st, 2 * mt + (wg & 1), odst + ps * 32768, ps,
                          gate[(wg & 1) * 64 + (tid & 63)], 3 + wg);
                if (ps == 0 && (fail & 1) && lane == 0) mbar_arrive(bars + 8 * B_OP);
            }
        f[0] = make_uint4(~0u, ~0u, ~0u, ~0u);
    }
    {
        int cta;
        asm volatile("mov.u32 %0, %%ctaid.x;" : "=r"(cta));
        const int nt = NTX, rt = 2 * MTX + (nt & 1), ct = nt >> 1, k0 = (wg & 1) * 2 + st;
        const uint4* src = (const uint4*)(g_o + rt * 65536 + 32768 + k0 * 2048) + (tid & 127);
        auto ldf = [&](int i) {
            asm volatile("ld.relaxed.gpu.global.v4.u32 {%0, %1, %2, %3}, [%4];" : "=r"(f[i].x), "=r"(f[i].y), "=r"(f[i].z), "=r"(f[i].w) : "l"(src + (i ^ ct) * 512) : "memory");
        };
#pragma unroll
        for (int i = 0; i < 4; i++)
            if (i || ((wg ^ nt) & 1)) ldf(i);
        if (st == 0 && !slow) named_sync(10, 256);
        for (uint32_t n = 0;; n++) {
            bool any = false;
#pragma unroll
            for (int i = 0; i < 4; i++)
                if (f[i].x == ~0u || f[i].y == ~0u || f[i].z == ~0u || f[i].w == ~0u) { ldf(i); any = true; }
            if (!__any_sync(~0u, any)) break;
            if (n > 0x800000u) __trap();
        }
        const uint32_t fa = sb + off_ol(wg) + w4 * 512 + (lane & 8) * 32 + (lane >> 4) * 128 + (lane & 7) * 16;
#pragma unroll
        for (int i = 0; i < 4; i++)
            asm volatile("stmatrix.sync.aligned.m8n8.x4.shared.b16 [%0], {%1, %2, %3, %4};"
                         ::"r"(fa + (i ^ ct) * 2048), "r"(f[i].x), "r"(f[i].y), "r"(f[i].z), "r"(f[i].w) : "memory");
        fence_async_s();
        named_sync(3 + wg, 128);
        if ((tid & 127) == 0) {
            const uint32_t t = atomicAdd((uint32_t*)misc + 1, 1);
            misc[40 + t] = (off_ol(wg) >> 4) | k0 << 23;
            mbar_arrive(bars + 8 * (B_OL + t));
        }
    }
}

typedef CUresult (*EncodeFn)(CUtensorMap*, CUtensorMapDataType, cuuint32_t, void*, const cuuint64_t*, const cuuint64_t*, const cuuint32_t*,
                             const cuuint32_t*, CUtensorMapInterleave, CUtensorMapSwizzle, CUtensorMapL2promotion, CUtensorMapFloatOOBfill);

void make_map(EncodeFn fn, CUtensorMap* m, const void* p, int rank, const cuuint64_t* dims, const cuuint64_t* strides, const cuuint32_t* box) {
    cuuint32_t es[4] = {1, 1, 1, 1};
    fn(m, CU_TENSOR_MAP_DATA_TYPE_BFLOAT16, rank, (void*)p, dims, strides, box, es, CU_TENSOR_MAP_INTERLEAVE_NONE, CU_TENSOR_MAP_SWIZZLE_128B,
       CU_TENSOR_MAP_L2_PROMOTION_L2_128B, CU_TENSOR_MAP_FLOAT_OOB_FILL_NONE);
}
void make_map2(EncodeFn fn, CUtensorMap* m, const void* p, int rows, int cols, int box_rows) {
    cuuint64_t dims[2] = {(cuuint64_t)cols, (cuuint64_t)rows}, strides[1] = {(cuuint64_t)cols * 2};
    cuuint32_t box[2] = {64, (cuuint32_t)box_rows};
    make_map(fn, m, p, 2, dims, strides, box);
}

}

extern "C" void kernel_launch(void* const* d_in, const int* in_sizes, int n_in, void* d_out, int out_size) {
    static EncodeFn fn = nullptr;
    if (!fn) {
        void* f = nullptr;
        cudaDriverEntryPointQueryResult qr;
        cudaGetDriverEntryPoint("cuTensorMapEncodeTiled", &f, cudaEnableDefault, &qr);
        fn = (EncodeFn)f;
        cudaFuncSetAttribute(fused_kernel, cudaFuncAttributeMaxDynamicSharedMemorySize, SMEM_BYTES);
    }
    CUtensorMap mx, mkv, mq, mo, mg, mu, md;
    make_map2(fn, &mx, d_in[0], S_, D_, 128);
    {
        cuuint64_t dims[3] = {512, 512, 3}, strides[2] = {3072, 1024};
        cuuint32_t box[3] = {64, 64, 2};
        make_map(fn, &mkv, d_in[1], 3, dims, strides, box);
    }
    make_map2(fn, &mq, d_in[1], D_, 3 * D_, 128);
    {
        cuuint64_t dims[4] = {512, 32, 2, 8}, strides[3] = {1024, 32768, 65536};
        cuuint32_t box[4] = {64, 32, 1, 8};
        make_map(fn, &mo, d_in[2], 4, dims, strides, box);
    }
    make_map2(fn, &mg, d_in[5], D_, F_, 256);
    make_map2(fn, &mu, d_in[6], D_, F_, 256);
    make_map2(fn, &md, d_in[7], F_, D_, 224);
    Params P;
    P.x = (const __nv_bfloat16*)d_in[0];
    P.wqkv = (const __nv_bfloat16*)d_in[1];
    P.w_r = (const __nv_bfloat16*)d_in[4];
    P.gate_w = (const __nv_bfloat16*)d_in[8];
    P.wg = (const __nv_bfloat16*)d_in[5];
    P.wu = (const __nv_bfloat16*)d_in[6];
    P.wd = (const __nv_bfloat16*)d_in[7];
    P.wo = (const __nv_bfloat16*)d_in[2];
    P.out = (__nv_bfloat16*)d_out;
    fused_kernel<<<NCTA, NTHR, SMEM_BYTES, cudaStreamPerThread>>>(mx, mkv, mq, mo, mg, mu, md, P);
}
```

```cpp
#include <cuda_runtime.h>
#include <cuda_bf16.h>
#include <cuda_fp16.h>
#include <cuda.h>
#include <stdint.h>

namespace {

constexpr int S_ = 2048, D_ = 512, F_ = 1792;
constexpr int NCTA = 132, NTHR = 640;
constexpr uint32_t SBASE = 0x400;
constexpr int SMEM_BYTES = 232448;

__host__ __device__ constexpr int off_w(int i) { return i == 0 ? 0 : 2048 + i * 16384; }
__host__ __device__ constexpr int off_x(int c) { return 100352 + (7 - c) * 16384; }
constexpr int SLOT = 34816;
constexpr int OFF_WOE = 4 * SLOT;
constexpr int OFF_STG = OFF_WOE + 65536;
__host__ __device__ constexpr int off_ol(int c) { return (c < 2 ? 3 * SLOT : OFF_STG) + (c & 1) * 8192; }
__host__ __device__ constexpr int off_q(int ps, int wg) {
    return OFF_STG + (ps == 0 ? 12288 - (wg & 1) * 8192 + (wg >> 1) * 2048 : wg >= 2 ? (wg & 1) * 8192 : 16384 + wg * 2048);
}
constexpr int OFF_BSEL = OFF_STG + 24576;
constexpr int OFF_INIT = OFF_BSEL + 512;
constexpr int OFF_MISC = 231424;
constexpr int M_STAGES = 6, M_STAGE_BYTES = 32768;
constexpr int OFF_XSEL = M_STAGES * M_STAGE_BYTES, OFF_HSEL = OFF_XSEL + 8192;
constexpr int B_AF = 0, B_AE = 8, B_QF = 14, B_AFREE = 18, B_KVP = 19, B_KF = 20, B_WL = 24, B_OE = 25, B_WOE = 26, B_K0 = 27, B_OP = 28, B_OL = 30, B_TRG = 35, B_GO = 36, B_HOLD = 38, B_CHK = 39;
constexpr unsigned long long BAR_CNT = 0x07000f0044700111ull;
constexpr int C_KV = 0, C_O = 8, C_R = 40, C_Y = 41, C_U = 42, NCNT = 50;

#define EXP_PAT 0x3333303033333030ull
constexpr unsigned long long PAT = EXP_PAT;
__host__ __device__ constexpr int pat_of(int i) { return (int)((PAT >> (4 * i)) & 15); }
constexpr float U0 = 12.f, OFF_C = 1.585497f, OFF_E = 2.083684f;
__host__ __device__ constexpr float init_of_t(int t) {
    return t == 0 ? U0 - 15.f + OFF_E : t == 2 ? 32.f + U0 + OFF_E - OFF_C : 32.f + U0;
}
#define TRGN 3
#define NPV 1
#define QA 0
#define PRE 4
#define PACE 8
#define GOJ 7
#define ARR 0
constexpr float BOUND_MAX = 19.2f;
constexpr float QSCALE = 0.25f * 1.4426950408889634f;

#define NTX ((cta & 3) | (cta >> 6 & 1) << 2)
#define MTX (cta >> 2 & 15)
__device__ __align__(1024) uint8_t g_kv[8 * 2 * 8 * 32768];
__device__ __align__(1024) uint8_t g_o[32 * 65536];
__device__ __align__(16) float g_mx[8 * 128];
__device__ __align__(16) float g_r[S_];
__device__ __align__(16) float g_g[S_];
__device__ __align__(16) float g_y[4 * 2 * D_];
__device__ __align__(16) int g_sel[4];
__device__ uint32_t g_cnt[NCNT * 32];
__device__ uint32_t g_epoch[NCTA];
#define TSTAMP(i)
#define CSTAMP(i)

__device__ __forceinline__ void wg_ss_n128_at(float (&d)[64], uint64_t da, uint64_t db, int acc) {
  asm volatile("{\n.reg .pred p;\nsetp.ne.b32 p, %66, 0;\n"
      "wgmma.mma_async.sync.aligned.m64n128k16.f32.bf16.bf16 {%0,%1,%2,%3,%4,%5,%6,%7,%8,%9,%10,%11,%12,%13,%14,%15,%16,%17,%18,%19,%20,%21,%22,%23,"
      "%24,%25,%26,%27,%28,%29,%30,%31,%32,%33,%34,%35,%36,%37,%38,%39,%40,%41,%42,%43,%44,%45,%46,%47,"
      "%48,%49,%50,%51,%52,%53,%54,%55,%56,%57,%58,%59,%60,%61,%62,%63}, %64, %65, p, 1, 1, 1, 0;\n}\n"
    : "+f"(d[0]), "+f"(d[1]), "+f"(d[2]), "+f"(d[3]), "+f"(d[4]), "+f"(d[5]), "+f"(d[6]), "+f"(d[7]), "+f"(d[8]), "+f"(d[9]), "+f"(d[10]), "+f"(d[11]),
      "+f"(d[12]), "+f"(d[13]), "+f"(d[14]), "+f"(d[15]), "+f"(d[16]), "+f"(d[17]), "+f"(d[18]), "+f"(d[19]), "+f"(d[20]), "+f"(d[21]), "+f"(d[22]), "+f"(d[23]),
      "+f"(d[24]), "+f"(d[25]), "+f"(d[26]), "+f"(d[27]), "+f"(d[28]), "+f"(d[29]), "+f"(d[30]), "+f"(d[31]), "+f"(d[32]), "+f"(d[33]), "+f"(d[34]), "+f"(d[35]),
      "+f"(d[36]), "+f"(d[37]), "+f"(d[38]), "+f"(d[39]), "+f"(d[40]), "+f"(d[41]), "+f"(d[42]), "+f"(d[43]), "+f"(d[44]), "+f"(d[45]), "+f"(d[46]), "+f"(d[47]),
      "+f"(d[48]), "+f"(d[49]), "+f"(d[50]), "+f"(d[51]), "+f"(d[52]), "+f"(d[53]), "+f"(d[54]), "+f"(d[55]), "+f"(d[56]), "+f"(d[57]), "+f"(d[58]), "+f"(d[59]),
      "+f"(d[60]), "+f"(d[61]), "+f"(d[62]), "+f"(d[63])
    : "l"(da), "l"(db), "r"(acc));
}
__device__ __forceinline__ void wg_ss_n128_bt(float (&d)[64], uint64_t da, uint64_t db, int acc) {
  asm volatile("{\n.reg .pred p;\nsetp.ne.b32 p, %66, 0;\n"
      "wgmma.mma_async.sync.aligned.m64n128k16.f32.bf16.bf16 {%0,%1,%2,%3,%4,%5,%6,%7,%8,%9,%10,%11,%12,%13,%14,%15,%16,%17,%18,%19,%20,%21,%22,%23,"
      "%24,%25,%26,%27,%28,%29,%30,%31,%32,%33,%34,%35,%36,%37,%38,%39,%40,%41,%42,%43,%44,%45,%46,%47,"
      "%48,%49,%50,%51,%52,%53,%54,%55,%56,%57,%58,%59,%60,%61,%62,%63}, %64, %65, p, 1, 1, 0, 1;\n}\n"
    : "+f"(d[0]), "+f"(d[1]), "+f"(d[2]), "+f"(d[3]), "+f"(d[4]), "+f"(d[5]), "+f"(d[6]), "+f"(d[7]), "+f"(d[8]), "+f"(d[9]), "+f"(d[10]), "+f"(d[11]),
      "+f"(d[12]), "+f"(d[13]), "+f"(d[14]), "+f"(d[15]), "+f"(d[16]), "+f"(d[17]), "+f"(d[18]), "+f"(d[19]), "+f"(d[20]), "+f"(d[21]), "+f"(d[22]), "+f"(d[23]),
      "+f"(d[24]), "+f"(d[25]), "+f"(d[26]), "+f"(d[27]), "+f"(d[28]), "+f"(d[29]), "+f"(d[30]), "+f"(d[31]), "+f"(d[32]), "+f"(d[33]), "+f"(d[34]), "+f"(d[35]),
      "+f"(d[36]), "+f"(d[37]), "+f"(d[38]), "+f"(d[39]), "+f"(d[40]), "+f"(d[41]), "+f"(d[42]), "+f"(d[43]), "+f"(d[44]), "+f"(d[45]), "+f"(d[46]), "+f"(d[47]),
      "+f"(d[48]), "+f"(d[49]), "+f"(d[50]), "+f"(d[51]), "+f"(d[52]), "+f"(d[53]), "+f"(d[54]), "+f"(d[55]), "+f"(d[56]), "+f"(d[57]), "+f"(d[58]), "+f"(d[59]),
      "+f"(d[60]), "+f"(d[61]), "+f"(d[62]), "+f"(d[63])
    : "l"(da), "l"(db), "r"(acc));
}
__device__ __forceinline__ void wg_ss_n8_at(float (&d)[4], uint64_t da, uint64_t db, int acc) {
  asm volatile("{\n.reg .pred p;\nsetp.ne.b32 p, %6, 0;\n"
      "wgmma.mma_async.sync.aligned.m64n8k16.f32.bf16.bf16 {%0,%1,%2,%3}, %4, %5, p, 1, 1, 1, 0;\n}\n"
    : "+f"(d[0]), "+f"(d[1]), "+f"(d[2]), "+f"(d[3])
    : "l"(da), "l"(db), "r"(acc));
}
__device__ __forceinline__ void wg_ss_qk(float (&d)[32], uint64_t da, uint64_t db, int acc) {
  asm volatile("{\n.reg .pred p;\nsetp.ne.b32 p, %34, 0;\n"
      "wgmma.mma_async.sync.aligned.m64n64k16.f32.f16.f16 {%0,%1,%2,%3,%4,%5,%6,%7,%8,%9,%10,%11,%12,%13,%14,%15,%16,%17,%18,%19,%20,%21,%22,%23,"
      "%24,%25,%26,%27,%28,%29,%30,%31}, %32, %33, p, 1, 1, 0, 1;\n}\n"
    : "+f"(d[0]), "+f"(d[1]), "+f"(d[2]), "+f"(d[3]), "+f"(d[4]), "+f"(d[5]), "+f"(d[6]), "+f"(d[7]), "+f"(d[8]), "+f"(d[9]), "+f"(d[10]), "+f"(d[11]),
      "+f"(d[12]), "+f"(d[13]), "+f"(d[14]), "+f"(d[15]), "+f"(d[16]), "+f"(d[17]), "+f"(d[18]), "+f"(d[19]), "+f"(d[20]), "+f"(d[21]), "+f"(d[22]), "+f"(d[23]),
      "+f"(d[24]), "+f"(d[25]), "+f"(d[26]), "+f"(d[27]), "+f"(d[28]), "+f"(d[29]), "+f"(d[30]), "+f"(d[31])
    : "l"(da), "l"(db), "r"(acc));
}
__device__ __forceinline__ void wg_rs_pv(uint32_t (&d)[6], uint32_t a0, uint32_t a1, uint32_t a2, uint32_t a3, uint64_t db) {
  asm volatile("wgmma.mma_async.sync.aligned.m64n24k16.f16.f16.f16 {%0,%1,%2,%3,%4,%5}, {%6,%7,%8,%9}, %10, 1, 1, 1, 0;\n"
    : "+r"(d[0]), "+r"(d[1]), "+r"(d[2]), "+r"(d[3]), "+r"(d[4]), "+r"(d[5])
    : "r"(a0), "r"(a1), "r"(a2), "r"(a3), "l"(db));
}
__device__ __forceinline__ void wg_rs_pv0(uint32_t (&d)[6], uint32_t a0, uint32_t a1, uint32_t a2, uint32_t a3, uint64_t db) {
  asm volatile("wgmma.mma_async.sync.aligned.m64n24k16.f16.f16.f16 {%0,%1,%2,%3,%4,%5}, {%6,%7,%8,%9}, %10, 0, 1, 1, 0;\n"
    : "+r"(d[0]), "+r"(d[1]), "+r"(d[2]), "+r"(d[3]), "+r"(d[4]), "+r"(d[5])
    : "r"(a0), "r"(a1), "r"(a2), "r"(a3), "l"(db));
}

__device__ __forceinline__ void wg_fence() { asm volatile("wgmma.fence.sync.aligned;" ::: "memory"); }
__device__ __forceinline__ void wg_commit() { asm volatile("wgmma.commit_group.sync.aligned;" ::: "memory"); }
template <int N> __device__ __forceinline__ void wg_wait() { asm volatile("wgmma.wait_group.sync.aligned %0;" ::"n"(N) : "memory"); }
template <int N> __device__ __forceinline__ void reg_fence(float (&r)[N]) {
#pragma unroll
    for (int i = 0; i < N; i++) asm volatile("" : "+f"(r[i])::"memory");
}
template <int N> __device__ __forceinline__ void reg_fence(uint32_t (&r)[N]) {
#pragma unroll
    for (int i = 0; i < N; i++) asm volatile("" : "+r"(r[i])::"memory");
}
__device__ __forceinline__ void mbar_init(uint32_t bar, int cnt) { asm volatile("mbarrier.init.shared::cta.b64 [%0], %1;" ::"r"(bar), "r"(cnt) : "memory"); }
__device__ __forceinline__ void mbar_expect(uint32_t bar, int bytes) { asm volatile("mbarrier.arrive.expect_tx.shared::cta.b64 _, [%0], %1;" ::"r"(bar), "r"(bytes) : "memory"); }
__device__ __forceinline__ void mbar_arrive(uint32_t bar) { asm volatile("mbarrier.arrive.shared::cta.b64 _, [%0];" ::"r"(bar) : "memory"); }
__device__ __forceinline__ void mbar_wait(uint32_t bar, int parity) {
    asm volatile("{\n.reg .pred p;\n.reg .u32 n;\nmov.u32 n, 0;\n"
                 "W_%=:\nmbarrier.try_wait.parity.shared::cta.b64 p, [%0], %1;\n@p bra D_%=;\n"
                 "add.u32 n, n, 1;\nsetp.lt.u32 p, n, 0x4000000;\n@p bra W_%=;\ntrap;\nD_%=:\n}" ::"r"(bar), "r"(parity) : "memory");
}
__device__ __forceinline__ void mbar_wait_u(uint32_t bar, int parity) {
    for (uint32_t n = 0;; n++) {
        uint32_t ok;
        asm volatile("{\n.reg .pred p;\nmbarrier.try_wait.parity.shared::cta.b64 p, [%1], %2;\nselp.u32 %0, 1, 0, p;\n}" : "=r"(ok) : "r"(bar), "r"(parity) : "memory");
        if (__all_sync(~0u, ok)) break;
        if (n > 0x4000000u) __trap();
    }
}
__device__ __forceinline__ uint32_t mbar_probe(uint32_t bar, int parity) {
    uint32_t ok;
    asm volatile("{\n.reg .pred p;\nmbarrier.test_wait.parity.shared::cta.b64 p, [%1], %2;\nselp.u32 %0, 1, 0, p;\n}" : "=r"(ok) : "r"(bar), "r"(parity) : "memory");
    return ok;
}
__device__ __forceinline__ void mbar_finish(uint32_t ok, uint32_t bar, int parity) {
    asm volatile("{\n.reg .pred p;\n.reg .u32 n;\nsetp.ne.u32 p, %2, 0;\n@p bra.uni D_%=;\nmov.u32 n, 0;\n"
                 "W_%=:\nmbarrier.try_wait.parity.shared::cta.b64 p, [%0], %1;\n@p bra.uni D_%=;\n"
                 "add.u32 n, n, 1;\nsetp.lt.u32 p, n, 0x4000000;\n@p bra.uni W_%=;\ntrap;\nD_%=:\n}" ::"r"(bar), "r"(parity), "r"(ok) : "memory");
}
__device__ __forceinline__ void tma2d(uint32_t dst, const CUtensorMap* m, int c0, int c1, uint32_t bar) {
    asm volatile("cp.async.bulk.tensor.2d.shared::cluster.global.mbarrier::complete_tx::bytes [%0], [%1, {%2, %3}], [%4];"
                 ::"r"(dst), "l"(m), "r"(c0), "r"(c1), "r"(bar) : "memory");
}
__device__ __forceinline__ void tma3d(uint32_t dst, const CUtensorMap* m, int c0, int c1, int c2, uint32_t bar) {
    asm volatile("cp.async.bulk.tensor.3d.shared::cluster.global.mbarrier::complete_tx::bytes [%0], [%1, {%2, %3, %4}], [%5];"
                 ::"r"(dst), "l"(m), "r"(c0), "r"(c1), "r"(c2), "r"(bar) : "memory");
}
__device__ __forceinline__ void tma4d(uint32_t dst, const CUtensorMap* m, int c0, int c1, int c2, int c3, uint32_t bar) {
    asm volatile("cp.async.bulk.tensor.4d.shared::cluster.global.mbarrier::complete_tx::bytes [%0], [%1, {%2, %3, %4, %5}], [%6];"
                 ::"r"(dst), "l"(m), "r"(c0), "r"(c1), "r"(c2), "r"(c3), "r"(bar) : "memory");
}
__device__ __forceinline__ void l2_prefetch(const void* src, int bytes) {
    asm volatile("cp.async.bulk.prefetch.L2.global [%0], %1;" ::"l"(src), "r"(bytes) : "memory");
}
__device__ __forceinline__ void bulk_ld(uint32_t dst, const void* src, int bytes, uint32_t bar) {
    asm volatile("cp.async.bulk.shared::cluster.global.mbarrier::complete_tx::bytes [%0], [%1], %2, [%3];"
                 ::"r"(dst), "l"(src), "r"(bytes), "r"(bar) : "memory");
}
__device__ __forceinline__ void fence_async_s() { asm volatile("fence.proxy.async.shared::cta;" ::: "memory"); }
__device__ __forceinline__ void fence_async_g() { asm volatile("fence.proxy.async.global;" ::: "memory"); }
__device__ __forceinline__ void cnt_arrive(int i) {
    asm volatile("red.release.gpu.global.add.u32 [%0], 1;" ::"l"(&g_cnt[i * 32]) : "memory");
}
__device__ __forceinline__ void cnt_wait(int i, uint32_t target) {
    for (uint32_t n = 0;; n++) {
        uint32_t v;
        asm volatile("ld.acquire.gpu.global.u32 %0, [%1];" : "=r"(v) : "l"(&g_cnt[i * 32]) : "memory");
        if ((int)(v - target) >= 0) break;
        if (n > 0x800000u) __trap();
    }
}
__device__ __forceinline__ void named_sync(int id, int n) { asm volatile("bar.sync %0, %1;" ::"r"(id), "r"(n) : "memory"); }
__device__ __forceinline__ uint32_t pack_h2(float lo, float hi) { uint32_t r; asm("cvt.rn.f16x2.f32 %0, %1, %2;" : "=r"(r) : "f"(hi), "f"(lo)); return r; }
__device__ __forceinline__ uint32_t pack_b2(float lo, float hi) { uint32_t r; asm("cvt.rn.bf16x2.f32 %0, %1, %2;" : "=r"(r) : "f"(hi), "f"(lo)); return r; }
__device__ __forceinline__ float2 h2f(uint32_t v) {
    float2 r;
    asm("{.reg .b16 a, b; mov.b32 {a, b}, %2; cvt.f32.f16 %0, a; cvt.f32.f16 %1, b;}" : "=f"(r.x), "=f"(r.y) : "r"(v));
    return r;
}
__device__ __forceinline__ float blo(uint32_t v) { return __uint_as_float(v << 16); }
__device__ __forceinline__ float bhi(uint32_t v) { return __uint_as_float(v & 0xffff0000u); }
__device__ __forceinline__ float rbf(float v) { return __bfloat162float(__float2bfloat16_rn(v)); }
__device__ __forceinline__ float frcp(float v) { float r; asm("rcp.approx.ftz.f32 %0, %1;" : "=f"(r) : "f"(v)); return r; }
__device__ __forceinline__ float sigmoidf_(float v) { return frcp(1.f + __expf(-v)); }
__host__ __device__ constexpr uint64_t mkdesc(uint32_t off, uint32_t lbo, uint32_t sbo, uint32_t swz) {
    return (uint64_t)((SBASE + off) >> 4) | ((uint64_t)(lbo >> 4) << 16) | ((uint64_t)(sbo >> 4) << 32) | ((uint64_t)swz << 62);
}

template <int T> __device__ __forceinline__ uint32_t exp_pair(float a, float b, uint32_t c3c) {
    uint32_t r;
    if (T == 0) {
        float x, y;
        asm("ex2.approx.ftz.f32 %0, %1;" : "=f"(x) : "f"(a));
        asm("ex2.approx.ftz.f32 %0, %1;" : "=f"(y) : "f"(b));
        r = pack_h2(x, y);
    } else {
        uint32_t y;
        asm("prmt.b32 %0, %1, %2, 0x6521;" : "=r"(y) : "r"(__float_as_uint(a)), "r"(__float_as_uint(b)));
        if (T == 2) {
            uint32_t m, e = y | 0x03ff03ffu;
            asm("lop3.b32 %0, %1, 0x03ff03ff, %2, 0xea;" : "=r"(m) : "r"(y), "r"(c3c));
            asm("fma.rn.relu.f16x2 %0, %1, %2, %3;" : "=r"(r) : "r"(y), "r"(m), "r"(e));
        } else {
            uint32_t z = 0xfbdafbdau - y, w;
            asm("{.reg .b32 c; mov.b32 c, 0x45304530; fma.rn.f16x2 %0, %1, %2, c;}" : "=r"(w) : "r"(y), "r"(z));
            asm("fma.rn.relu.f16x2 %0, %1, %2, %1;" : "=r"(r) : "r"(y), "r"(w));
        }
    }
    return r;
}
template <int I> struct ExpLoop {
    static __device__ __forceinline__ void run(float (&s)[32], uint32_t (&p)[16], uint32_t c3c) {
        p[I] = exp_pair<pat_of(I)>(s[2 * I], s[2 * I + 1], c3c);
        ExpLoop<I + 1>::run(s, p, c3c);
    }
};
template <> struct ExpLoop<16> { static __device__ __forceinline__ void run(float (&)[32], uint32_t (&)[16], uint32_t) {} };
__device__ __forceinline__ void init_s(float (&s)[32], uint32_t a) {
#pragma unroll
    for (int j = 0; j < 8; j++)
        asm volatile("ld.shared.v4.f32 {%0, %1, %2, %3}, [%4];" : "=f"(s[4 * j]), "=f"(s[4 * j + 1]), "=f"(s[4 * j + 2]), "=f"(s[4 * j + 3])
                     : "r"(a + 16 * j));
}
__device__ __forceinline__ uint32_t hfma2(uint32_t a, uint32_t b, uint32_t c) { uint32_t r; asm("fma.rn.f16x2 %0, %1, %2, %3;" : "=r"(r) : "r"(a), "r"(b), "r"(c)); return r; }
__device__ __forceinline__ bool wg_any(int id, bool v) {
    uint32_t r;
    asm volatile("{\n.reg .pred p, q;\nsetp.ne.u32 q, %2, 0;\nbar.red.or.pred p, %1, 128, q;\nselp.u32 %0, 1, 0, p;\n}" : "=r"(r) : "r"(id), "r"((uint32_t)v) : "memory");
    return r;
}

__device__ __noinline__ void attn_slow(uint8_t* scr, const __nv_bfloat16* x, const __nv_bfloat16* w, int head, int rowtile, uint8_t* dst, int frag, float gate, int bar) {
    const int r = threadIdx.x & 63, hf = (threadIdx.x >> 6) & 1;
    float q[16], o[16], m = -INFINITY, l = 0.f;
#pragma unroll
    for (int d = 0; d < 16; d++) o[d] = 0.f;
    for (int c = -1; c < 32; c++) {
        const __nv_bfloat16* xr = x + ((c < 0 ? rowtile : c) * 64 + r) * D_;
        const __nv_bfloat16* wc = w + (c < 0 ? 0 : 512 + hf * 512) + head * 16;
        float a[16];
#pragma unroll
        for (int d = 0; d < 16; d++) a[d] = 0.f;
        for (int k2 = 0; k2 < 256; k2++) {
            const uint32_t xv = *(const uint32_t*)(xr + k2 * 2);
#pragma unroll
            for (int kk = 0; kk < 2; kk++) {
                const float xf = kk ? bhi(xv) : blo(xv);
                const uint4 w0 = *(const uint4*)(wc + (k2 * 2 + kk) * 1536), w1 = *(const uint4*)(wc + (k2 * 2 + kk) * 1536 + 8);
                const uint32_t ws[8] = {w0.x, w0.y, w0.z, w0.w, w1.x, w1.y, w1.z, w1.w};
#pragma unroll
                for (int d = 0; d < 8; d++) { a[2 * d] += xf * blo(ws[d]); a[2 * d + 1] += xf * bhi(ws[d]); }
            }
        }
        if (c < 0) {
#pragma unroll
            for (int d = 0; d < 16; d++) q[d] = rbf(a[d]);
            continue;
        }
        named_sync(bar, 128);
#pragma unroll
        for (int d = 0; d < 8; d++) ((uint32_t*)(scr + r * 64 + hf * 32))[d] = pack_b2(a[2 * d], a[2 * d + 1]);
        named_sync(bar, 128);
        for (int k = hf * 32; k < hf * 32 + 32; k++) {
            const uint32_t* kv = (const uint32_t*)(scr + k * 64);
            float s = 0.f;
#pragma unroll
            for (int d = 0; d < 8; d++) { s += q[2 * d] * blo(kv[d]); s += q[2 * d + 1] * bhi(kv[d]); }
            s = rbf(rbf(s) * 0.25f);
            const float mn = fmaxf(m, s), cr = __expf(m - mn), p = __expf(s - mn);
            l = l * cr + p;
            m = mn;
#pragma unroll
            for (int d = 0; d < 8; d++) { o[2 * d] = o[2 * d] * cr + p * blo(kv[8 + d]); o[2 * d + 1] = o[2 * d + 1] * cr + p * bhi(kv[8 + d]); }
        }
    }
    float* f = (float*)scr;
    named_sync(bar, 128);
    f[(hf * 64 + r) * 2] = m; f[(hf * 64 + r) * 2 + 1] = l;
    named_sync(bar, 128);
    const float m2 = f[((hf ^ 1) * 64 + r) * 2], l2 = f[((hf ^ 1) * 64 + r) * 2 + 1], mn = fmaxf(m, m2), cr = __expf(m - mn);
    const float sc = gate * cr * frcp(l * cr + l2 * __expf(m2 - mn));
    named_sync(bar, 128);
#pragma unroll
    for (int d = 0; d < 8; d++) f[(d * 2 + hf) * 64 + r] = (hf ? o[d] : o[8 + d]) * sc;
    named_sync(bar, 128);
    float e[8];
#pragma unroll
    for (int d = 0; d < 8; d++) e[d] = (hf ? o[8 + d] : o[d]) * sc + f[(d * 2 + (hf ^ 1)) * 64 + r];
#pragma unroll
    for (int t = 0; t < 4; t++)
        *(uint32_t*)(dst + (frag ? (r >> 4) * 512 + (r & 7) * 64 + t * 16 + hf * 8 + ((r >> 3) & 1) * 4 : (r >> 3) * 256 + hf * 128 + (r & 7) * 16 + t * 4)) =
            pack_b2(e[2 * t], e[2 * t + 1]);
    named_sync(bar, 128);
}

template <int V> struct IC { static constexpr int v = V; };
struct Params {
    const __nv_bfloat16 *x, *wqkv, *w_r, *gate_w, *wg, *wu, *wd, *wo;
    __nv_bfloat16* out;
};

__device__ __forceinline__ void mod_cta(uint8_t* smem, uint32_t sb, const Params& P, const CUtensorMap* mg, const CUtensorMap* mu,
                                        const CUtensorMap* md) {
    const int tid = threadIdx.x, lane = tid & 31, warp = tid >> 5, wg = tid >> 7, part = blockIdx.x - 128;
    const uint32_t bars = sb + OFF_MISC;
    constexpr int NBOX = 44;
    auto issue = [&](int i) {
        const int st = i % M_STAGES;
        const uint32_t bar = bars + 8 * (B_AF + st), dst = sb + st * M_STAGE_BYTES;
        if (i < 28) {
            const int j = i < 24 ? (i >> 3) * 2 + (i & 1) : 6, q = i < 24 ? (i >> 1) & 3 : i & 3;
            mbar_expect(bar, 32768);
            tma2d(dst, (q & 2) ? mu : mg, part * 448 + j * 64, (q & 1) * 256, bar);
        } else {
            mbar_expect(bar, 28672);
            tma2d(dst, md, (((i - 28) >> 2) * 2 + (i & 1)) * 64, part * 448 + ((i >> 1) & 1) * 224, bar);
        }
    };
    __syncthreads();
    if (tid == 512) {
        const uint32_t ep = g_epoch[blockIdx.x] + 1;
        for (int i = 0; i < M_STAGES; i++) issue(i);
        g_epoch[blockIdx.x] = ep;
        cnt_wait(C_R, 128 * ep);
    }
    for (int i = tid; i < 4096; i += NTHR) ((uint32_t*)(smem + OFF_XSEL))[i] = 0;
    __syncthreads();
    unsigned long long b1 = 0, b2 = 0;
    if (tid < 512) {
        const float4 rv = __ldcg((const float4*)(g_r + tid * 4));
        const float rr[4] = {rv.x, rv.y, rv.z, rv.w};
#pragma unroll
        for (int j = 0; j < 4; j++) {
            uint32_t u = __float_as_uint(rr[j]);
            u = (u & 0x80000000u) ? ~u : (u | 0x80000000u);
            const unsigned long long k = ((unsigned long long)u << 32) | (uint32_t)(~(tid * 4 + j));
            if (k > b1) { b2 = b1; b1 = k; } else if (k > b2) b2 = k;
        }
    }
    auto merge = [&](int o) {
        const unsigned long long c1 = __shfl_xor_sync(~0u, b1, o), c2 = __shfl_xor_sync(~0u, b2, o);
        const unsigned long long hi = b1 > c1 ? b1 : c1, lo = b1 > c1 ? c1 : b1, s2 = b2 > c2 ? b2 : c2;
        b1 = hi; b2 = lo > s2 ? lo : s2;
    };
    for (int o = 16; o; o >>= 1) merge(o);
    unsigned long long* red = (unsigned long long*)(smem + OFF_MISC + 512);
    if (lane == 0) { red[warp * 2] = b1; red[warp * 2 + 1] = b2; }
    __syncthreads();
    b1 = red[(lane & 15) * 2]; b2 = red[(lane & 15) * 2 + 1];
    for (int o = 8; o; o >>= 1) merge(o);
    const int i0 = (int)(~(uint32_t)b1), i1 = (int)(~(uint32_t)b2);
    if (tid < 128) {
        const int t = tid >> 6, kc = tid & 63;
        *(uint4*)(smem + OFF_XSEL + kc * 128 + t * 16) = *(const uint4*)(P.x + (t ? i1 : i0) * D_ + kc * 8);
    }
    if (part == 0 && tid == 0) {
        g_sel[0] = i0; g_sel[1] = i1;
        g_sel[2] = __float_as_int(rbf(sigmoidf_(__ldcg(g_r + i0))));
        g_sel[3] = __float_as_int(rbf(sigmoidf_(__ldcg(g_r + i1))));
    }
    fence_async_s();
    __syncthreads();
    if (tid == 512) {
        for (int i = M_STAGES; i < NBOX; i++) {
            mbar_wait(bars + 8 * (B_AE + i % M_STAGES), (i / M_STAGES - 1) & 1);
            issue(i);
        }
    } else if (wg < 2) {
        const int w4 = warp & 3, g = lane >> 2;
        auto box = [&](float (&acc)[4], int i, int nk, uint32_t boff, int first) {
            const int st = i % M_STAGES;
            mbar_wait(bars + 8 * (B_AF + st), (i / M_STAGES) & 1);
            const uint64_t da = mkdesc(0, 8192, 1024, 1) + st * (M_STAGE_BYTES >> 4), db = mkdesc(0, 128, 256, 0) + (boff >> 4);
            reg_fence(acc);
            wg_fence();
            for (int k = 0; k < nk; k++) wg_ss_n8_at(acc, da + k * 128, db + k * 16, !(first && k == 0));
            wg_commit();
            wg_wait<0>();
            reg_fence(acc);
            named_sync(3 + wg, 128);
            if ((tid & 127) == 0) mbar_arrive(bars + 8 * (B_AE + st));
        };
#pragma unroll 1
        for (int j = wg; j < 7; j += 2) {
            float ag[4] = {0, 0, 0, 0}, au[4] = {0, 0, 0, 0};
            const int i = (j >> 1) * 8 + wg, di = j < 6 ? 2 : 1;
            box(ag, i, 16, OFF_XSEL, 1); box(ag, i + di, 16, OFF_XSEL + 4096, 0);
            box(au, i + 2 * di, 16, OFF_XSEL, 1); box(au, i + 3 * di, 16, OFF_XSEL + 4096, 0);
            if ((lane & 3) == 0) {
#pragma unroll
                for (int e = 0; e < 4; e++) {
                    const float gv = rbf(ag[e]), h = rbf(gv * sigmoidf_(gv)) * rbf(au[e]);
                    const int f = j * 64 + w4 * 16 + (e >> 1) * 8 + g;
                    *(__nv_bfloat16*)(smem + OFF_HSEL + (f >> 3) * 128 + (e & 1) * 16 + (f & 7) * 2) = __float2bfloat16_rn(h);
                }
            }
        }
        fence_async_s();
        named_sync(1, 256);
#pragma unroll 1
        for (int j = wg; j < 8; j += 2) {
            float a[4] = {0, 0, 0, 0};
            const int i = 28 + (j >> 1) * 4 + wg;
            box(a, i, 14, OFF_HSEL, 1); box(a, i + 2, 14, OFF_HSEL + 14 * 256, 0);
            if ((lane & 3) == 0) {
#pragma unroll
                for (int e = 0; e < 4; e++) g_y[(part * 2 + (e & 1)) * D_ + j * 64 + w4 * 16 + (e >> 1) * 8 + g] = a[e];
            }
        }
        named_sync(1, 256);
        if (tid == 0) { cnt_arrive(C_Y); TSTAMP(1); }
    }
}

__global__ void __launch_bounds__(NTHR, 1)
fused_kernel(const __grid_constant__ CUtensorMap mx, const __grid_constant__ CUtensorMap mkv, const __grid_constant__ CUtensorMap mq,
             const __grid_constant__ CUtensorMap mo, const __grid_constant__ CUtensorMap mg,
             const __grid_constant__ CUtensorMap mu, const __grid_constant__ CUtensorMap md, const __grid_constant__ Params P) {
    extern __shared__ __align__(1024) uint8_t smem[];
    constexpr uint32_t sb = SBASE, bars = sb + OFF_MISC;
    const int tid = threadIdx.x, lane = tid & 31, warp = __shfl_sync(~0u, tid >> 5, 0), wg = warp >> 2, w4 = warp & 3;
    const int cta = blockIdx.x;
    volatile uint32_t* misc = (volatile uint32_t*)(smem + OFF_MISC + 320);
    volatile float* gate = (volatile float*)(smem + OFF_MISC + 512);
    const int nt = NTX, mt = MTX;
    const int rt = 2 * mt + (nt & 1), ct = nt >> 1;

    auto a_chunk = [&](int kc) {
        const uint32_t bar = bars + 8 * (B_AF + kc);
        mbar_expect(bar, 32768);
        tma2d(sb + off_x(kc), &mx, kc * 64, mt * 128, bar);
        if (kc < 6) tma3d(sb + off_w(kc), &mkv, nt * 64, kc * 64, 1, bar);
    };
    if (lane == 0) {
        if (warp == 16) {
            TSTAMP(0);
#pragma unroll
            for (int i = 0; i < 8; i++) mbar_init(bars + 8 * (B_AF + i), 1);
            fence_async_s();
            if (cta < 128) {
#pragma unroll
                for (int kc = 0; kc < PRE; kc++) a_chunk(kc);
                TSTAMP(15);
            }
        } else if (wg < 4) {
            const uint32_t c = cta < 128 ? (uint32_t)(BAR_CNT >> (warp * 4)) & 15 : 0;
            mbar_init(bars + 8 * (8 + 2 * warp), c + 1);
            mbar_init(bars + 8 * (9 + 2 * warp), c + 1);
            fence_async_s();
            misc[1] = 0; misc[2] = 0;
            if ((uint32_t)__cvta_generic_to_shared(smem) != SBASE) __trap();
        }
    }
    __syncwarp();
    if (cta >= 128) {
        mod_cta(smem, sb, P, &mg, &mu, &md);
        return;
    }

    if (wg == 4) {
        const uint32_t ep = g_epoch[cta] + 1;
        named_sync(7, NTHR);
        if (warp == 17) {
        if (lane == 0) {
            mbar_wait(bars + 8 * B_KVP, 0);
            TSTAMP(7);
            cnt_arrive(C_KV + nt);
            cnt_wait(C_R, 128 * ep);
            cnt_wait(C_KV + nt, 16 * ep);
            mbar_wait(bars + 8 * B_AFREE, 0);
        }
        __syncwarp();
        ((float4*)gate)[lane] = __ldcg((const float4*)(g_g + mt * 128) + lane);
        {
            const uint4 v = __ldcg((const uint4*)(g_mx + nt * 128) + lane);
            uint32_t m = max(max(v.x, v.y), max(v.z, v.w));
            m = max(m, __shfl_xor_sync(~0u, m, 1));
            m = max(m, __shfl_xor_sync(~0u, m, 2));
            const float k2 = __uint_as_float(__shfl_sync(~0u, m, (lane & 3) * 4)), vm = __uint_as_float(__shfl_sync(~0u, m, 16 + (lane & 3) * 4));
            const float q2 = __uint_as_float(misc[8 + (lane & 3)]);
            if (lane < 4) misc[4 + lane] = q2 * k2 <= BOUND_MAX * BOUND_MAX && q2 <= 65536.f && k2 <= 65536.f && vm >= 0.03125f ? 0x43800000u : 0x7f800000u;
        }
        __syncwarp();
        if (lane == 0) {
            mbar_arrive(bars + 8 * B_CHK);
            l2_prefetch(P.wg + cta * 7168, 14336); l2_prefetch(P.wu + cta * 7168, 14336); l2_prefetch(P.wd + cta * 7168, 14336);
            l2_prefetch(P.wo + cta * 2048, 4096);
            mbar_wait(bars + 8 * (B_KF + 3), 0);
            mbar_expect(bars + 8 * B_WOE, 65536);
            for (int j = 0; j < 2; j++) tma4d(sb + OFF_WOE + j * 32768, &mo, ct * 128 + j * 64, 0, 0, 0, bars + 8 * B_WOE);
        }
        __syncwarp();
        }
        if (warp == 16) {
        auto kv_stage = [&](int s) {
            const uint32_t bar = bars + 8 * (B_KF + (s & 3)), dst = sb + (s & 3) * SLOT;
            const uint8_t* src = g_kv + (nt * 16 + s) * 32768;
            mbar_expect(bar, 32768);
            bulk_ld(dst, src, 16384, bar);
            bulk_ld(dst + 18432, src + 16384, 16384, bar);
        };
        if (lane == 0) {
#pragma unroll
            for (int kc = PRE; kc < 8; kc++) {
                if (kc == PACE) mbar_wait(bars + 8 * B_AF, 0);
                a_chunk(kc);
            }
            g_epoch[cta] = ep;
#pragma unroll 1
            for (int i = 0; i < 6; i++) {
                mbar_wait(bars + 8 * (B_AE + i), 0);
                if (i < 2) tma3d(sb + off_w(i), &mkv, nt * 64, (6 + i) * 64, 1, bars + 8 * (B_AF + 6 + i));
                else {
                    mbar_expect(bars + 8 * (B_QF + i - 2), 16384);
                    tma2d(sb + off_w(i), &mq, nt * 64, (i - 2) * 128, bars + 8 * (B_QF + i - 2));
                }
            }
            mbar_wait(bars + 8 * B_GO, 0);
            TSTAMP(12);
            if (mt < 8) cnt_arrive(C_U + nt);
            mbar_arrive(bars + 8 * B_HOLD);
            TSTAMP(3);
            cnt_wait(C_U + nt, 8 * ep);
            TSTAMP(4);
            fence_async_g();
            {
                const uint8_t* src = g_kv + nt * 16 * 32768;
                mbar_expect(bars + 8 * B_K0, 4096);
                bulk_ld(sb, src, 2048, bars + 8 * B_K0);
                bulk_ld(sb + 24576, src + 22528, 2048, bars + 8 * B_K0);
                mbar_expect(bars + 8 * B_KF, 28672);
                bulk_ld(sb + 2048, src + 2048, 14336, bars + 8 * B_KF);
                bulk_ld(sb + 18432, src + 16384, 6144, bars + 8 * B_KF);
                bulk_ld(sb + 26624, src + 24576, 8192, bars + 8 * B_KF);
            }
            mbar_wait(bars + 8 * B_AFREE, 0);
            for (int s = 1; s <= GOJ / 4; s++) kv_stage(s);
            cnt_wait(C_KV + nt, 16 * ep);
            fence_async_g();
            for (int s = GOJ / 4 + 1; s < 4; s++) kv_stage(s);
            TSTAMP(19);
#pragma unroll 1
            for (int s = 4; s < 16; s++) {
                mbar_wait(bars + 8 * (B_KF + ((s - 2) & 3)), ((s - 2) >> 2) & 1);
                if (s == 8) mbar_wait(bars + 8 * B_CHK, 0);
                kv_stage(s);
            }
            TSTAMP(18);
            mbar_arrive(bars + 8 * B_KF);
            mbar_wait(bars + 8 * B_OP, 0);
            cnt_arrive(C_O + mt);
            cnt_wait(C_Y, 4 * ep);
        }
        __syncwarp();
        }
        named_sync(9, 128);
        float acc[64];
        {
            const int4 sel = __ldcg((const int4*)g_sel);
            uint32_t* bsel = (uint32_t*)(smem + OFF_BSEL);
            if ((sel.x >> 6) == rt || (sel.y >> 6) == rt) {
                const int t = w4 >> 1, c = ct * 128 + (tid & 63) * 2;
                const float rs = __int_as_float(t ? sel.w : sel.z);
                const uint32_t xv = *(const uint32_t*)(P.x + (t ? sel.y : sel.x) * D_ + c);
                float y0 = 0.f, y1 = 0.f;
#pragma unroll
                for (int pp = 0; pp < 4; pp++) {
                    const float2 v = __ldcg((const float2*)(g_y + (pp * 2 + t) * D_ + c));
                    y0 += v.x; y1 += v.y;
                }
                bsel[tid - 512] = pack_b2(blo(xv) + rbf(rbf(y0) * rs), bhi(xv) + rbf(rbf(y1) * rs));
                named_sync(9, 128);
            }
#pragma unroll
            for (int h = 0; h < 2; h++) {
                const int lr = (nt & 1) * 64 + w4 * 16 + (lane >> 2) + 8 * h, r = mt * 128 + lr;
                const float g = 1.f - gate[lr];
                const uint32_t* xp = (r == sel.x ? bsel : r == sel.y ? bsel + 64 : (const uint32_t*)(P.x + r * D_ + ct * 128)) + (lane & 3);
#pragma unroll
                for (int j = 0; j < 16; j++) { const uint32_t xv = xp[j * 4]; acc[4 * j + 2 * h] = g * blo(xv); acc[4 * j + 2 * h + 1] = g * bhi(xv); }
            }
        }
        __syncwarp();
        if (tid == 512) {
            TSTAMP(17);
            mbar_wait(bars + 8 * (B_KF + 2), 1);
            cnt_wait(C_O + mt, 8 * ep);
            fence_async_g();
            mbar_expect(bars + 8 * B_OE, 32768);
            bulk_ld(sb, g_o + rt * 65536, 32768, bars + 8 * B_OE);
            mbar_expect(bars + 8 * B_WL, 65536);
            for (int j = 0; j < 2; j++) {
                mbar_wait(bars + 8 * (B_KF + 3 - 3 * j), 1 - j);
                tma4d(sb + (1 + j) * SLOT, &mo, ct * 128 + j * 64, 0, 1, 0, bars + 8 * B_WL);
            }
            mbar_wait(bars + 8 * B_TRG, 0);
            TSTAMP(16);
        }
        __syncwarp();
        named_sync(9, 128);
        mbar_wait_u(bars + 8 * B_WOE, 0);
        mbar_wait_u(bars + 8 * B_OE, 0);
        reg_fence(acc);
        wg_fence();
#pragma unroll
        for (int k = 0; k < 16; k++) wg_ss_n128_bt(acc, mkdesc(k * 2048, 128, 256, 0), mkdesc(OFF_WOE + k * 2048, 32768, 1024, 1), 1);
        wg_commit();
        mbar_wait_u(bars + 8 * B_WL, 0);
        if (tid == 512) TSTAMP(8);
#pragma unroll
        for (int t = 0; t < 4; t++) {
            mbar_wait_u(bars + 8 * (B_OL + t), 0);
            if (tid == 512 && t == 1) TSTAMP(13);
            if (tid == 512 && t == 3) TSTAMP(9);
            const uint32_t c = __shfl_sync(~0u, misc[40 + t], 0);
            const uint64_t da = mkdesc(0, 128, 256, 0) + (c & 0xffff), db = mkdesc(SLOT, SLOT, 1024, 1) + (c >> 16);
            wg_fence();
#pragma unroll
            for (int i = 0; i < 4; i++) wg_ss_n128_bt(acc, da + i * 128, db + i * 512, 1);
            wg_commit();
        }
        wg_wait<0>();
        reg_fence(acc);
        if (tid == 512) TSTAMP(10);
        const uint32_t stg = sb + 3 * SLOT + 18432 + w4 * 4096, sa = stg + (lane & 15) * 128;
#pragma unroll
        for (int j = 0; j < 16; j += 2) {
            uint32_t v[4];
#pragma unroll
            for (int e = 0; e < 4; e++) v[e] = pack_b2(acc[4 * j + 2 * e], acc[4 * j + 2 * e + 1]);
            asm volatile("stmatrix.sync.aligned.m8n8.x4.shared.b16 [%0], {%1, %2, %3, %4};"
                         ::"r"(sa + (j >> 3) * 2048 + ((((j & 7) + (lane >> 4)) ^ (lane & 7)) << 4)), "r"(v[0]), "r"(v[1]), "r"(v[2]), "r"(v[3]) : "memory");
        }
        __syncwarp();
        uint4* od = (uint4*)(P.out + (rt * 64 + w4 * 16 + (lane >> 4)) * D_ + ct * 128) + (lane & 15);
#pragma unroll
        for (int i = 0; i < 8; i++) {
            const int r = 2 * i + (lane >> 4);
            uint4 v;
            asm volatile("ld.shared.v4.u32 {%0, %1, %2, %3}, [%4];" : "=r"(v.x), "=r"(v.y), "=r"(v.z), "=r"(v.w)
                         : "r"(stg + (lane & 8) * 256 + r * 128 + (((lane & 7) ^ (r & 7)) << 4)) : "memory");
            od[i * 128] = v;
        }
        if (tid == 512) TSTAMP(11);
        return;
    }

    if (wg < 2) {
        if (wg == 0) {
            *(uint4*)(smem + 16384 + tid * 16) = make_uint4(0x3c003c00u, 0x3c003c00u, 0x3c003c00u, 0x3c003c00u);
            fence_async_s();
        }
        const int st = w4 & 1, cg = mt & 7;
        uint8_t* const dst = g_kv + ((nt * 2 + (w4 >> 1)) * 8 + (mt >> 3) * 4) * 32768 + st * 16384 + lane * 4 + (wg ? cg * 128 : st * 6144 + cg * 256);
        const int o00 = st ? 0 : 12288;
        auto kslot = [&](int j, int h) { return (uint32_t*)(dst + (j >> 2) * 32768 + ((j >> 1) & 1) * 6144 + (j & 1) * 2048 + h * 128); };
        auto vslot = [&](int j, int h) { return (uint32_t*)(dst + (j >> 2) * 32768 + ((j & 2) ? 4096 + h * 6144 : o00 + h * 2048) + (j & 1) * 1024); };
        named_sync(7, NTHR);
        float acc[64];
#pragma unroll
        for (int kc = 0; kc < 8; kc++) {
            mbar_wait_u(bars + 8 * (B_AF + kc), 0);
            if (kc == 0 && tid == 0) TSTAMP(1);
            const uint64_t da = mkdesc(off_w(kc % 6), 8192, 1024, 1) + wg * 512, db = mkdesc(off_x(kc), 16, 1024, 1);
            wg_fence();
#pragma unroll
            for (int kk = 0; kk < 4; kk++) wg_ss_n128_at(acc, da + kk * 128, db + kk * 2, kc + kk > 0);
            wg_commit();
            if (kc >= 1 && kc <= 6) {
                wg_wait<1>();
                if ((tid & 127) == 0) mbar_arrive(bars + 8 * (B_AE + kc - 1));
            }
        }
        wg_wait<0>();
        reg_fence(acc);
        if (tid == 0) TSTAMP(2);
        uint32_t mxv;
        const bool urgent = mt < 8 && w4 < 2;
        auto put = [&](auto j0, auto j1) {
            if (wg == 0) {
#pragma unroll
                for (int i = 4 * decltype(j0)::v; i < 4 * decltype(j1)::v; i += 2)
                    *kslot(i >> 2, i >> 1 & 1) = i >= 4 ? pack_h2(acc[i] - acc[i - 4], acc[i + 1] - acc[i - 3]) : pack_h2(acc[i], acc[i + 1]);
            } else {
#pragma unroll
                for (int i = 4 * decltype(j0)::v; i < 4 * decltype(j1)::v; i += 2) *vslot(i >> 2, i >> 1 & 1) = pack_h2(acc[i], acc[i + 1]);
            }
        };
        if (!QA) asm volatile("bar.arrive 8, 512;" ::: "memory");
        if (urgent) put(IC<0>(), IC<GOJ + 1>());
        if (QA) asm volatile("bar.arrive 8, 512;" ::: "memory");
        __syncwarp();
        if (lane == 0) mbar_arrive(bars + 8 * B_GO);
        if (mt < 8) mbar_wait_u(bars + 8 * B_HOLD, 0);
        if (!urgent) put(IC<0>(), IC<GOJ + 1>());
        put(IC<GOJ + 1>(), IC<16>());
        if (wg == 0) {
            uint32_t n[16];
#pragma unroll
            for (int j = 0; j < 16; j++) n[j] = pack_b2(acc[4 * j] * acc[4 * j] + acc[4 * j + 2] * acc[4 * j + 2], acc[4 * j + 1] * acc[4 * j + 1] + acc[4 * j + 3] * acc[4 * j + 3]);
            auto fold = [&](auto oc) {
                constexpr int o = decltype(oc)::v;
                const bool up = lane & (2 * o);
#pragma unroll
                for (int i = 0; i < o; i++) {
                    const uint32_t t = __shfl_xor_sync(~0u, up ? n[i] : n[i + o], 2 * o), k = up ? n[i + o] : n[i];
                    asm("add.bf16x2 %0, %1, %2;" : "=r"(n[i]) : "r"(t), "r"(k));
                }
            };
            fold(IC<8>()); fold(IC<4>()); fold(IC<2>());
            mxv = max(max(n[0] << 16, n[0] & 0xffff0000u), max(n[1] << 16, n[1] & 0xffff0000u));
        } else {
            float mm = 0.f;
#pragma unroll
            for (int i = 0; i < 64; i++) mm = fmaxf(mm, fabsf(acc[i]));
            mxv = __float_as_uint(mm);
        }
        mxv = __reduce_max_sync(~0u, mxv);
        if (lane == 0) { g_mx[nt * 128 + warp * 16 + mt] = __uint_as_float(mxv); mbar_arrive(bars + 8 * B_KVP); }
        named_sync(1, 512);
    } else {
        {
            const int row0 = cta * 16 + (warp - 8) * 2;
            uint4 xv[2][2], wr[2], wgt[2];
#pragma unroll
            for (int c = 0; c < 2; c++) {
#pragma unroll
                for (int r = 0; r < 2; r++) xv[r][c] = *(const uint4*)(P.x + (row0 + r) * D_ + c * 256 + lane * 8);
                wr[c] = *(const uint4*)(P.w_r + c * 256 + lane * 8);
                wgt[c] = *(const uint4*)(P.gate_w + c * 256 + lane * 8);
            }
            named_sync(7, NTHR);
                auto dot8 = [](uint4 a, uint4 b) {
                return blo(a.x) * blo(b.x) + bhi(a.x) * bhi(b.x) + blo(a.y) * blo(b.y) + bhi(a.y) * bhi(b.y) +
                       blo(a.z) * blo(b.z) + bhi(a.z) * bhi(b.z) + blo(a.w) * blo(b.w) + bhi(a.w) * bhi(b.w);
            };
#pragma unroll
            for (int r = 0; r < 2; r++) {
                float a = dot8(xv[r][0], wr[0]) + dot8(xv[r][1], wr[1]), b = dot8(xv[r][0], wgt[0]) + dot8(xv[r][1], wgt[1]);
#pragma unroll
                for (int o = 16; o; o >>= 1) { a += __shfl_xor_sync(~0u, a, o); b += __shfl_xor_sync(~0u, b, o); }
                if (lane == 0) { g_r[row0 + r] = rbf(a); g_g[row0 + r] = sigmoidf_(b); }
            }
#pragma unroll
            for (int i = 0; i < 2; i++)
                *((uint4*)(g_o + (2 * mt + i) * 65536 + 32768 + nt * 4096) + (tid - 256)) = make_uint4(~0u, ~0u, ~0u, ~0u);
            named_sync(2, 256);
            if (tid == 256) cnt_arrive(C_R);
            __syncwarp();
        }
        uint32_t n[16];
        named_sync(8, 512);
        if (wg == 2) {
            float acc[64];
#pragma unroll
            for (int kc = 0; kc < 8; kc++) {
                if (!(kc & 1)) mbar_wait_u(bars + 8 * (B_QF + (kc >> 1)), 0);
                mbar_wait_u(bars + 8 * (B_AF + kc), 0);
                const uint64_t da = mkdesc(off_w(2 + (kc >> 1)) + (kc & 1) * 8192, 8192, 1024, 1), db = mkdesc(off_x(kc), 16, 1024, 1);
                wg_fence();
#pragma unroll
                for (int kk = 0; kk < 4; kk++) wg_ss_n128_at(acc, da + kk * 128, db + kk * 2, kc + kk > 0);
                wg_commit();
            }
            wg_wait<0>();
            reg_fence(acc);
            if (tid == 256) TSTAMP(14);
            named_sync(5, 128);
#pragma unroll
            for (int j = 0; j < 16; j += 2) {
                uint32_t v[4];
#pragma unroll
                for (int e = 0; e < 4; e++) v[e] = pack_h2(acc[4 * j + 2 * e] * QSCALE, acc[4 * j + 2 * e + 1] * QSCALE);
                asm volatile("stmatrix.sync.aligned.m8n8.x4.trans.shared.b16 [%0], {%1, %2, %3, %4};"
                             ::"r"(sb + off_q(w4 >> 1, (w4 & 1) * 2 + (j >> 3)) + (j & 7) * 256 + lane * 16), "r"(v[0]), "r"(v[1]), "r"(v[2]), "r"(v[3]) : "memory");
                n[j] = hfma2(v[0], v[0], hfma2(v[1], v[1], 0));
                n[j + 1] = hfma2(v[2], v[2], hfma2(v[3], v[3], 0));
            }
            if (w4 == 0) *(float*)(smem + OFF_INIT + lane * 4) = (PAT >> (lane >> 1) * 4 & 15) == 0 ? init_of_t(0) : (PAT >> (lane >> 1) * 4 & 15) == 2 ? init_of_t(2) : init_of_t(3);
            fence_async_s();
        }
        named_sync(1, 512);
        if (wg == 2) {
            auto fold = [&](auto oc) {
                constexpr int o = decltype(oc)::v;
                const bool up = lane & (2 * o);
#pragma unroll
                for (int i = 0; i < o; i++) {
                    const uint32_t t = __shfl_xor_sync(~0u, up ? n[i] : n[i + o], 2 * o), k = up ? n[i + o] : n[i];
                    asm("add.f16x2 %0, %1, %2;" : "=r"(n[i]) : "r"(t), "r"(k));
                }
            };
            fold(IC<8>()); fold(IC<4>()); fold(IC<2>());
            const uint32_t m = __reduce_max_sync(~0u, max(max(n[0] & 0xffff, n[0] >> 16), max(n[1] & 0xffff, n[1] >> 16)));
            if (lane == 0) misc[8 + w4] = __float_as_uint(h2f(m).x);
        } else {
#pragma unroll
            for (int i = 1; i < 4; i++) *(uint4*)(smem + i * SLOT + 16384 + (tid - 384) * 16) = make_uint4(0x3c003c00u, 0x3c003c00u, 0x3c003c00u, 0x3c003c00u);
        }
        fence_async_s();
        __syncwarp();
        if (lane == 0) mbar_arrive(bars + 8 * B_AFREE);
    }

    const int st = wg >> 1;
    uint8_t* const odst = g_o + (2 * mt + (wg & 1)) * 65536 + (nt * 2 + st) * 2048;
    uint32_t fail = 0;
    uint4 f[4];
    {
        float s[32];
        uint32_t o[6], o4 = 0, o5 = 0;
        uint64_t dq = mkdesc(0, 128, 256, 0) + (off_q(0, wg) >> 4);
        uint32_t c3c = 0x3c003c00u;
        asm volatile("" : "+r"(c3c));
        const uint64_t dk0 = mkdesc(0, 128, 256, 0) + st * (24576 >> 4);
        const uint64_t dv0 = mkdesc(12288, 128, 2048, 0) + st * (4096 >> 4), dw0 = mkdesc(4096, 128, 6144, 0) + st * (12288 >> 4);
        const bool sig = (tid & 127) == 0;
        uint32_t par = 0;
        auto rtid = []() { uint32_t t; asm volatile("mov.u32 %0, %%tid.x;" : "=r"(t)); return t & 127; };
        const uint32_t park = sb + off_q(1, wg) + (st ? 2048 : 4096);
        const uint32_t ia = sb + OFF_INIT + misc[1];
        init_s(s, ia);
        if (sig) mbar_arrive(bars + 8 * B_KF);
        mbar_wait_u(bars + 8 * B_K0, 0);
        if (tid == 0) { TSTAMP(5); CSTAMP(30); }
        wg_fence();
        wg_ss_qk(s, dq, dk0, 1);
        wg_commit();
        wg_wait<0>();
        reg_fence(s);
#define ATT_BLOCK(I, U, DN)                                                                                       \
    {                                                                                                             \
        uint32_t p[16], ok;                                                                                       \
        if (U == 3) { if (I == 3) par ^= 1; ok = mbar_probe(nb, par); }                                           \
        if (I + U == 0) ok = mbar_probe(bars + 8 * B_KF, par);                                                    \
        ExpLoop<0>::run(s, p, c3c);                                                                               \
        if (I == 3 && U == 3) {                     \
            init_s(s, ia);                                                                                        \
            if (seg & 1) dq = mkdesc(0, 128, 256, 0) + (off_q(1, wg) >> 4);                                       \
        }                                                                                                         \
        if (I + U == 0) mbar_finish(ok, bars + 8 * B_KF, par);                                                    \
        if (U == 3) mbar_finish(ok, nb, par);                                                                     \
        wg_fence();                                                                                               \
        wg_ss_qk(s, dq, DN, 1);                                                                                   \
        const uint64_t dp = (U < 2 ? dv : dw) + (U & 1) * 64;                                                     \
        if (NPV == 0) wg_commit();                                                                                \
        if (U == 0 && I == 0) wg_rs_pv0(o, p[0], p[1], p[2], p[3], dp);                                           \
        else wg_rs_pv(o, p[0], p[1], p[2], p[3], dp);                                                             \
        if (NPV == 1) wg_commit();                                                                                \
        wg_rs_pv(o, p[4], p[5], p[6], p[7], dp + 16);                                                             \
        if (NPV == 2) wg_commit();                                                                                \
        wg_rs_pv(o, p[8], p[9], p[10], p[11], dp + 32);                                                           \
        if (NPV == 3) wg_commit();                                                                                \
        wg_rs_pv(o, p[12], p[13], p[14], p[15], dp + 48);                                                         \
        wg_commit();                                                                                              \
        wg_wait<(I == 3 && U == 3) ? 0 : 1>();                                                                    \
        if (U == ARR && sig) mbar_arrive(nb);                                                                     \
        reg_fence(s);                                                                                             \
    }
#define ATT_STAGE(I)                                                                                              \
    {                                                                                                             \
        const uint64_t dk = dk0 + I * (SLOT >> 4), dv = dv0 + I * (SLOT >> 4), dw = dw0 + I * (SLOT >> 4);        \
        constexpr uint32_t nb = bars + 8 * (B_KF + ((I + 1) & 3));                                                \
        ATT_BLOCK(I, 0, dk + 128)                                                                                 \
        ATT_BLOCK(I, 1, dk + 384)                                                                                 \
        ATT_BLOCK(I, 2, dk + 512)                                                                                 \
        ATT_BLOCK(I, 3, dk0 + ((I + 1) & 3) * (SLOT >> 4))                                                        \
    }
#pragma unroll 1
        for (int seg = 0;; seg++) {
            ATT_STAGE(0) ATT_STAGE(1) ATT_STAGE(2) ATT_STAGE(3)
            reg_fence(o);
            const uint32_t t = rtid();
            if (!(seg & 1)) {
                asm volatile("st.shared.v4.u32 [%0], {%1, %2, %3, %4};" ::"r"(park + t * 16), "r"(o[0]), "r"(o[1]), "r"(o[2]), "r"(o[3]) : "memory");
                o4 = o[4]; o5 = o[5];
            } else {
                uint32_t o2[6];
                asm volatile("ld.shared.v4.u32 {%0, %1, %2, %3}, [%4];" : "=r"(o2[0]), "=r"(o2[1]), "=r"(o2[2]), "=r"(o2[3]) : "r"(park + t * 16) : "memory");
                o2[4] = o4; o2[5] = o5;
#pragma unroll
                for (int i = 0; i < 6; i++) asm("add.f16x2 %0, %0, %1;" : "+r"(o2[i]) : "r"(o[i]));
                const uint32_t ga = sb + OFF_MISC + 512 + (wg & 1) * 256 + (t >> 5) * 64 + (t & 28);
                float g0, g1, lmin;
                asm volatile("ld.shared.f32 %0, [%3];\nld.shared.f32 %1, [%3 + 32];\nld.shared.f32 %2, [%4];"
                             : "=f"(g0), "=f"(g1), "=f"(lmin) : "r"(ga), "r"(sb + OFF_MISC + 336 + 4 * (seg - 1 + st)));
                uint32_t w[4];
                bool ok;
                auto fin = [&](auto oc) {
                    constexpr int a = decltype(oc)::v;
                    const float l0 = h2f(o2[4 - 2 * a]).x, l1 = h2f(o2[5 - 2 * a]).x;
                    g0 *= frcp(l0); g1 *= frcp(l1);
#pragma unroll
                    for (int i = 0; i < 4; i++) {
                        const float2 v = h2f(o2[a + i]);
                        w[i] = pack_b2(v.x * ((i & 1) ? g1 : g0), v.y * ((i & 1) ? g1 : g0));
                    }
                    ok = l0 >= lmin && l1 >= lmin;
                };
                if (st) fin(IC<2>()); else fin(IC<0>());
                uint32_t z = 0;
#pragma unroll
                for (int i = 0; i < 6; i++) z = hfma2(o2[i], 0, z);
                ok = __all_sync(~0u, ok && z == 0);
                if (seg == 3) {
                    f[0] = make_uint4(w[0], w[1], w[2], w[3]);
                    if (ok) *(uint4*)(odst + 32768 + t * 16) = f[0];
                    else fail |= 2;
                    break;
                }
                if (!ok) fail |= 1;
                else {
#pragma unroll
                    for (int i = 0; i < 4; i++) ((uint32_t*)odst)[(t >> 5) * 128 + (t & 31) + (i >> 1) * 32 + (i & 1) * 64] = w[i];
                    __syncwarp();
                    if ((t & 31) == 0) mbar_arrive(bars + 8 * B_OP);
                }
            }
        }
        if (tid == 0) { TSTAMP(6); CSTAMP(31); }
    }
    if (lane == 0 && atomicAdd((uint32_t*)misc + 2, 1) == TRGN) mbar_arrive(bars + 8 * B_TRG);
    const bool slow = wg_any(3 + wg, fail);
    if (slow) {
        if (st == 0) named_sync(10, 256);
        for (int ps = 0; ps < 2; ps++)
            if (wg_any(3 + wg, (fail >> ps) & 1)) {
                attn_slow(smem + OFF_STG + (st ? (wg & 1) * 8192 : 16384 + wg * 4096), P.x, P.wqkv, nt * 4 + 2 * ps + st, 2 * mt + (wg & 1), odst + ps * 32768, ps,
                          gate[(wg & 1) * 64 + (tid & 63)], 3 + wg);
                if (ps == 0 && (fail & 1) && lane == 0) mbar_arrive(bars + 8 * B_OP);
            }
        f[0] = make_uint4(~0u, ~0u, ~0u, ~0u);
    }
    {
        int cta;
        asm volatile("mov.u32 %0, %%ctaid.x;" : "=r"(cta));
        const int nt = NTX, rt = 2 * MTX + (nt & 1), ct = nt >> 1, k0 = (wg & 1) * 2 + st;
        const uint4* src = (const uint4*)(g_o + rt * 65536 + 32768 + k0 * 2048) + (tid & 127);
        auto ldf = [&](int i) {
            asm volatile("ld.relaxed.gpu.global.v4.u32 {%0, %1, %2, %3}, [%4];" : "=r"(f[i].x), "=r"(f[i].y), "=r"(f[i].z), "=r"(f[i].w) : "l"(src + (i ^ ct) * 512) : "memory");
        };
#pragma unroll
        for (int i = 0; i < 4; i++)
            if (i || ((wg ^ nt) & 1)) ldf(i);
        if (st == 0 && !slow) named_sync(10, 256);
        for (uint32_t n = 0;; n++) {
            bool any = false;
#pragma unroll
            for (int i = 0; i < 4; i++)
                if (f[i].x == ~0u || f[i].y == ~0u || f[i].z == ~0u || f[i].w == ~0u) { ldf(i); any = true; }
            if (!__any_sync(~0u, any)) break;
            if (n > 0x800000u) __trap();
        }
        const uint32_t fa = sb + off_ol(wg) + w4 * 512 + (lane & 8) * 32 + (lane >> 4) * 128 + (lane & 7) * 16;
#pragma unroll
        for (int i = 0; i < 4; i++)
            asm volatile("stmatrix.sync.aligned.m8n8.x4.shared.b16 [%0], {%1, %2, %3, %4};"
                         ::"r"(fa + (i ^ ct) * 2048), "r"(f[i].x), "r"(f[i].y), "r"(f[i].z), "r"(f[i].w) : "memory");
        fence_async_s();
        named_sync(3 + wg, 128);
        if ((tid & 127) == 0) {
            const uint32_t t = atomicAdd((uint32_t*)misc + 1, 1);
            misc[40 + t] = (off_ol(wg) >> 4) | k0 << 23;
            mbar_arrive(bars + 8 * (B_OL + t));
        }
    }
}

typedef CUresult (*EncodeFn)(CUtensorMap*, CUtensorMapDataType, cuuint32_t, void*, const cuuint64_t*, const cuuint64_t*, const cuuint32_t*,
                             const cuuint32_t*, CUtensorMapInterleave, CUtensorMapSwizzle, CUtensorMapL2promotion, CUtensorMapFloatOOBfill);

void make_map(EncodeFn fn, CUtensorMap* m, const void* p, int rank, const cuuint64_t* dims, const cuuint64_t* strides, const cuuint32_t* box) {
    cuuint32_t es[4] = {1, 1, 1, 1};
    fn(m, CU_TENSOR_MAP_DATA_TYPE_BFLOAT16, rank, (void*)p, dims, strides, box, es, CU_TENSOR_MAP_INTERLEAVE_NONE, CU_TENSOR_MAP_SWIZZLE_128B,
       CU_TENSOR_MAP_L2_PROMOTION_L2_128B, CU_TENSOR_MAP_FLOAT_OOB_FILL_NONE);
}
void make_map2(EncodeFn fn, CUtensorMap* m, const void* p, int rows, int cols, int box_rows) {
    cuuint64_t dims[2] = {(cuuint64_t)cols, (cuuint64_t)rows}, strides[1] = {(cuuint64_t)cols * 2};
    cuuint32_t box[2] = {64, (cuuint32_t)box_rows};
    make_map(fn, m, p, 2, dims, strides, box);
}

}

extern "C" void kernel_launch(void* const* d_in, const int* in_sizes, int n_in, void* d_out, int out_size) {
    static EncodeFn fn = nullptr;
    if (!fn) {
        void* f = nullptr;
        cudaDriverEntryPointQueryResult qr;
        cudaGetDriverEntryPoint("cuTensorMapEncodeTiled", &f, cudaEnableDefault, &qr);
        fn = (EncodeFn)f;
        cudaFuncSetAttribute(fused_kernel, cudaFuncAttributeMaxDynamicSharedMemorySize, SMEM_BYTES);
    }
    CUtensorMap mx, mkv, mq, mo, mg, mu, md;
    make_map2(fn, &mx, d_in[0], S_, D_, 128);
    {
        cuuint64_t dims[3] = {512, 512, 3}, strides[2] = {3072, 1024};
        cuuint32_t box[3] = {64, 64, 2};
        make_map(fn, &mkv, d_in[1], 3, dims, strides, box);
    }
    make_map2(fn, &mq, d_in[1], D_, 3 * D_, 128);
    {
        cuuint64_t dims[4] = {512, 32, 2, 8}, strides[3] = {1024, 32768, 65536};
        cuuint32_t box[4] = {64, 32, 1, 8};
        make_map(fn, &mo, d_in[2], 4, dims, strides, box);
    }
    make_map2(fn, &mg, d_in[5], D_, F_, 256);
    make_map2(fn, &mu, d_in[6], D_, F_, 256);
    make_map2(fn, &md, d_in[7], F_, D_, 224);
    Params P;
    P.x = (const __nv_bfloat16*)d_in[0];
    P.wqkv = (const __nv_bfloat16*)d_in[1];
    P.w_r = (const __nv_bfloat16*)d_in[4];
    P.gate_w = (const __nv_bfloat16*)d_in[8];
    P.wg = (const __nv_bfloat16*)d_in[5];
    P.wu = (const __nv_bfloat16*)d_in[6];
    P.wd = (const __nv_bfloat16*)d_in[7];
    P.wo = (const __nv_bfloat16*)d_in[2];
    P.out = (__nv_bfloat16*)d_out;
    fused_kernel<<<NCTA, NTHR, SMEM_BYTES, cudaStreamPerThread>>>(mx, mkv, mq, mo, mg, mu, md, P);
}
```
